```python
import torch

def _softmax(x, axis=-1):
    return torch.softmax(x, dim=axis)

def _gelu(x):
    return torch.nn.functional.gelu(x, approximate='tanh')

def _silu(x):
    return torch.nn.functional.silu(x)

def _sigmoid(x):
    return torch.sigmoid(x)

def _layernorm(x, axis=-1, eps=1e-05):
    m = x.mean(dim=axis, keepdim=True)
    v = x.var(dim=axis, keepdim=True, unbiased=False)
    return (x - m) / torch.sqrt(v + eps)

def _scatter_add(tgt, idx, src, axis=0):
    return tgt.clone().index_add_(axis, idx, src)

def _segment_sum(src, seg, n):
    out = torch.zeros((n,) + src.shape[1:], dtype=src.dtype)
    return out.index_add_(0, seg, src)

def _pad(x, pw):
    flat = tuple((v for pair in reversed(pw) for v in pair))
    return torch.nn.functional.pad(x, flat)
kernel_name = 'concat_heads__sliding_block__memory_aug_recurrent_mem_tr__prompt'

def setup_inputs():

    _w = lambda a: (lambda t: t.to(torch.bfloat16) if t.is_floating_point() else t)(torch.as_tensor(a))

    def _A_setup():
        B, S, D = (1, 2048, 1024)
        return {'x': _w((lambda *s: torch.randn(*s, dtype=torch.bfloat16) * 0.2)(B, S, D)), 'wqkv': _w((lambda *s: torch.randn(*s, dtype=torch.bfloat16) * 0.2)(D, 3 * D)), 'wo': _w((lambda *s: torch.randn(*s, dtype=torch.bfloat16) * 0.05)(D, D))}
    _A_in = _A_setup()

    def _B_setup():
        B, S, Dm = (1, 2048, 1024)
        H, Dh = (32, 128)
        M, seg = (8, 32)
        seg = min(seg, S)
        S = S // seg * seg
        return {'x': _w((lambda *s: torch.randn(*s, dtype=torch.bfloat16) * 0.05)(B, S, Dm)), 'mem0': _w((lambda *s: torch.randn(*s, dtype=torch.bfloat16) * 1.6)(B, M, Dm)), 'Wq': _w((lambda *s: torch.randn(*s, dtype=torch.bfloat16) * 0.8)(Dm, H, Dh) * Dm ** (-0.5)), 'Wk': _w((lambda *s: torch.randn(*s, dtype=torch.bfloat16) * 0.8)(Dm, H, Dh) * Dm ** (-0.5)), 'Wv': _w((lambda *s: torch.randn(*s, dtype=torch.bfloat16) * 1.6)(Dm, H, Dh) * Dm ** (-0.5)), 'Wo': _w((lambda *s: torch.randn(*s, dtype=torch.bfloat16) * 1.6)(H, Dh, Dm) * (H * Dh) ** (-0.5)), 'seg_len': seg}
    _B_in = _B_setup()
    return {'A_x': _A_in['x'], 'A_wqkv': _A_in['wqkv'], 'A_wo': _A_in['wo'], 'B_x': _B_in['x'], 'B_mem0': _B_in['mem0'], 'B_Wq': _B_in['Wq'], 'B_Wk': _B_in['Wk'], 'B_Wv': _B_in['Wv'], 'B_Wo': _B_in['Wo'], 'B_seg_len': _B_in['seg_len']}

def reference(A_x, A_wqkv, A_wo, B_x, B_mem0, B_Wq, B_Wk, B_Wv, B_Wo, B_seg_len):

    def _A_ref(x, wqkv, wo):
        B, S, D = x.shape
        H = 32
        Dh = D // H
        W = 256
        qkv = (lambda x, *d: x.permute(*d))((x @ wqkv).reshape(B, S, 3, H, Dh), 2, 0, 3, 1, 4)
        q, k, v = (qkv[0], qkv[1], qkv[2])
        scores = torch.einsum('bhqd,bhkd->bhqk', q, k) * Dh ** (-0.5)
        idx = torch.arange(S)
        mask = (idx[:, None] - idx[None, :] >= 0) & (idx[:, None] - idx[None, :] < W)
        scores = torch.where(mask[None, None], scores, -1000000000.0)
        p = _softmax(scores, axis=-1)
        o = torch.einsum('bhqk,bhkd->bhqd', p, v)
        return (lambda x, *d: x.permute(*d))(o, 0, 2, 1, 3).reshape(B, S, D) @ wo

    def _B_ref(x, mem0, Wq, Wk, Wv, Wo, seg_len):
        B, S, Dm = x.shape
        H, Dh = (Wq.shape[1], Wq.shape[2])
        M = mem0.shape[1]
        scale = Dh ** (-0.5)
        n_seg = S // seg_len
        L = M + seg_len
        idx = torch.arange(L)
        mask = (idx[:, None] < M) | (idx[:, None] >= idx[None, :])
        mem = mem0
        outs = []
        for s in range(n_seg):
            xs = x[:, s * seg_len:(s + 1) * seg_len, :].clone()
            h = torch.concatenate([mem, xs], axis=1)
            q = torch.einsum('btd,dhe->bhte', h, Wq)
            k = torch.einsum('btd,dhe->bhte', h, Wk)
            v = torch.einsum('btd,dhe->bhte', h, Wv)
            scores = torch.einsum('bhqe,bhke->bhqk', q, k) * scale
            scores = torch.where(mask[None, None], scores, -1000000000.0)
            p = _softmax(scores, axis=-1)
            o = torch.einsum('bhqk,bhke->bhqe', p, v)
            o = torch.einsum('bhte,hed->btd', o, Wo)
            mem = o[:, :M, :].clone()
            outs.append(o[:, M:, :])
        return torch.concatenate(outs, axis=1)
    a = _A_ref(A_x, A_wqkv, A_wo)
    b = _B_ref(B_x, B_mem0, B_Wq, B_Wk, B_Wv, B_Wo, B_seg_len)
    return torch.concatenate([a, b], axis=-1)
```

```cpp
#include <cuda_runtime.h>
#include <cuda_bf16.h>
#include <cuda.h>
#include <stdint.h>
#include <stdio.h>

typedef __nv_bfloat16 bf16;

#define DEVI __device__ __forceinline__
#define CUT_STYLE 1
#define SPIN_LIMIT (1u << 24)

DEVI uint32_t smem_u32(const void* p) { return (uint32_t)__cvta_generic_to_shared(p); }
DEVI uint32_t mapa(uint32_t a, uint32_t r) {
    uint32_t o; asm("mapa.shared::cluster.u32 %0, %1, %2;" : "=r"(o) : "r"(a), "r"(r)); return o;
}
DEVI void mbar_init(uint32_t bar, uint32_t cnt) {
    asm volatile("mbarrier.init.shared::cta.b64 [%0], %1;" ::"r"(bar), "r"(cnt) : "memory");
}
DEVI void mbar_arrive(uint32_t bar) {
    asm volatile("mbarrier.arrive.shared::cta.b64 _, [%0];" ::"r"(bar) : "memory");
}
DEVI void mbar_arrive_cluster(uint32_t bar_cluster_addr) {
    asm volatile("mbarrier.arrive.relaxed.cluster.shared::cluster.b64 _, [%0];" ::"r"(bar_cluster_addr) : "memory");
}
DEVI void mbar_expect_tx(uint32_t bar, uint32_t bytes) {
    asm volatile("mbarrier.arrive.expect_tx.shared::cta.b64 _, [%0], %1;" ::"r"(bar), "r"(bytes) : "memory");
}
DEVI void mbar_wait(uint32_t bar, uint32_t parity) {
    asm volatile(
        "{\n.reg .pred p;\n.reg .u32 c;\n"
        "mbarrier.try_wait.parity.shared::cta.b64 p, [%0], %1;\n@p bra.uni LD;\nmov.u32 c, 0;\n"
        "LW:\nmbarrier.try_wait.parity.shared::cta.b64 p, [%0], %1;\n@p bra.uni LD;\n"
        "add.u32 c, c, 1;\nsetp.lt.u32 p, c, 4000000;\n@p bra.uni LW;\ntrap;\nLD:\n}"
        ::"r"(bar), "r"(parity) : "memory");
}
DEVI void mbar_spin(uint32_t bar, uint32_t parity) {
    asm volatile("{\n.reg .pred p;\nLW:\nmbarrier.try_wait.parity.shared::cta.b64 p, [%0], %1;\n@!p bra.uni LW;\n}"
                 ::"r"(bar), "r"(parity) : "memory");
}
DEVI void mbar_wait1(uint32_t bar, uint32_t parity) {
    asm volatile(
        "{\n.reg .pred p;\n.reg .u32 c;\nmov.u32 c, 0;\n"
        "LW:\nmbarrier.try_wait.parity.shared::cta.b64 p, [%0], %1;\n@p bra LD;\n"
        "add.u32 c, c, 1;\nsetp.lt.u32 p, c, 4000000;\n@p bra LW;\ntrap;\nLD:\n}"
        ::"r"(bar), "r"(parity) : "memory");
}
DEVI void mbar_arrive_w(uint32_t bar) {
    asm volatile("{\n.reg .pred p;\nelect.sync _|p, 0xffffffff;\n@p mbarrier.arrive.shared::cta.b64 _, [%0];\n}" ::"r"(bar) : "memory");
}
DEVI void mbar_arrive_cluster_w(uint32_t bar) {
    asm volatile("{\n.reg .pred p;\nelect.sync _|p, 0xffffffff;\n@p mbarrier.arrive.relaxed.cluster.shared::cluster.b64 _, [%0];\n}" ::"r"(bar) : "memory");
}
DEVI void mbar_expect_tx_w(uint32_t bar, uint32_t bytes) {
    asm volatile("{\n.reg .pred p;\nelect.sync _|p, 0xffffffff;\n@p mbarrier.arrive.expect_tx.shared::cta.b64 _, [%0], %1;\n}" ::"r"(bar), "r"(bytes) : "memory");
}
DEVI void tma2d_w(uint32_t dst, const CUtensorMap* m, int c0, int c1, uint32_t bar) {
    asm volatile("{\n.reg .pred p;\nelect.sync _|p, 0xffffffff;\n"
                 "@p cp.async.bulk.tensor.2d.shared::cluster.global.mbarrier::complete_tx::bytes [%0], [%1, {%3, %4}], [%2];\n}"
                 ::"r"(dst), "l"(m), "r"(bar), "r"(c0), "r"(c1) : "memory");
}
DEVI void tma3d_w(uint32_t dst, const CUtensorMap* m, int c0, int c1, int c2, uint32_t bar) {
    asm volatile("{\n.reg .pred p;\nelect.sync _|p, 0xffffffff;\n"
                 "@p cp.async.bulk.tensor.3d.shared::cluster.global.mbarrier::complete_tx::bytes [%0], [%1, {%3, %4, %5}], [%2];\n}"
                 ::"r"(dst), "l"(m), "r"(bar), "r"(c0), "r"(c1), "r"(c2) : "memory");
}
DEVI void tma5d_w(uint32_t dst, const CUtensorMap* m, int c2, int c3, uint32_t bar) {
    asm volatile("{\n.reg .pred p;\nelect.sync _|p, 0xffffffff;\n"
                 "@p cp.async.bulk.tensor.5d.shared::cluster.global.mbarrier::complete_tx::bytes [%0], [%1, {%5, %5, %3, %4, %5}], [%2];\n}"
                 ::"r"(dst), "l"(m), "r"(bar), "r"(c2), "r"(c3), "r"(0) : "memory");
}
DEVI void tma2d_prefetch_w(const CUtensorMap* m, int c0, int c1) {
    asm volatile("{\n.reg .pred p;\nelect.sync _|p, 0xffffffff;\n@p cp.async.bulk.prefetch.tensor.2d.L2.global [%0, {%1, %2}];\n}"
                 ::"l"(m), "r"(c0), "r"(c1) : "memory");
}
DEVI void bulk_load_w(uint32_t dst, const void* src, uint32_t bytes, uint32_t bar) {
    asm volatile("{\n.reg .pred p;\nelect.sync _|p, 0xffffffff;\n@p mbarrier.arrive.expect_tx.shared::cta.b64 _, [%3], %2;\n"
                 "@p cp.async.bulk.shared::cluster.global.mbarrier::complete_tx::bytes [%0], [%1], %2, [%3];\n}"
                 ::"r"(dst), "l"(src), "r"(bytes), "r"(bar) : "memory");
}
DEVI void bulk_mcast_w(uint32_t dst, const void* src, uint32_t bytes, uint32_t bar) {
    asm volatile("{\n.reg .pred p;\n.reg .b16 m;\nmov.b16 m, 7;\nelect.sync _|p, 0xffffffff;\n"
                 "@p cp.async.bulk.shared::cluster.global.mbarrier::complete_tx::bytes.multicast::cluster [%0], [%1], %2, [%3], m;\n}"
                 ::"r"(dst), "l"(src), "r"(bytes), "r"(bar) : "memory");
}
DEVI void bulk_store_w(void* dst, uint32_t src, uint32_t bytes) {
    asm volatile("{\n.reg .pred p;\nelect.sync _|p, 0xffffffff;\n@p cp.async.bulk.global.shared::cta.bulk_group [%0], [%1], %2;\n}"
                 ::"l"(dst), "r"(src), "r"(bytes) : "memory");
}
DEVI void stsm4t(uint32_t addr, uint32_t a, uint32_t b, uint32_t c, uint32_t d) {
    asm volatile("stmatrix.sync.aligned.m8n8.x4.trans.shared.b16 [%0], {%1,%2,%3,%4};" ::"r"(addr), "r"(a), "r"(b), "r"(c), "r"(d) : "memory");
}
DEVI void st_async32(uint32_t a, uint32_t x, uint32_t bar) {
    asm volatile("st.async.weak.shared::cluster.mbarrier::complete_tx::bytes.b32 [%0], %1, [%2];" ::"r"(a), "r"(x), "r"(bar) : "memory");
}
DEVI void bulk_s2c_w(uint32_t dst_cluster, uint32_t src, uint32_t bytes, uint32_t bar_cluster) {
    asm volatile("{\n.reg .pred p;\nelect.sync _|p, 0xffffffff;\n"
                 "@p cp.async.bulk.shared::cluster.shared::cta.mbarrier::complete_tx::bytes [%0], [%1], %2, [%3];\n}"
                 ::"r"(dst_cluster), "r"(src), "r"(bytes), "r"(bar_cluster) : "memory");
}
DEVI void st_relaxed32_if(bool c, void* p, uint32_t x) {
    asm volatile("{\n.reg .pred p;\nsetp.ne.u32 p, %2, 0;\n@p st.relaxed.gpu.global.b32 [%0], %1;\n}" ::"l"(p), "r"(x), "r"((uint32_t)c) : "memory");
}
DEVI void red_add_if(bool c, unsigned* p, unsigned v) {
    asm volatile("{\n.reg .pred p;\nsetp.ne.u32 p, %2, 0;\n@p red.relaxed.gpu.global.add.u32 [%0], %1;\n}" ::"l"(p), "r"(v), "r"((uint32_t)c) : "memory");
    __syncwarp();
}
DEVI void red_add_w(unsigned* p, unsigned v) {
    asm volatile("{\n.reg .pred p;\nelect.sync _|p, 0xffffffff;\n@p red.relaxed.gpu.global.add.u32 [%0], %1;\n}" ::"l"(p), "r"(v) : "memory");
    __syncwarp();
}
DEVI void fence_proxy_async() { asm volatile("fence.proxy.async.shared::cta;" ::: "memory"); }
DEVI void bar_sync(int id, int n) { asm volatile("bar.sync %0, %1;" ::"r"(id), "r"(n) : "memory"); }
DEVI void bar_arrive(int id, int n) { asm volatile("bar.arrive %0, %1;" ::"r"(id), "r"(n) : "memory"); }
DEVI void cluster_sync() {
    asm volatile("barrier.cluster.arrive.relaxed.aligned;\nbarrier.cluster.wait.aligned;" ::: "memory");
}
DEVI void tma2d(uint32_t dst, const CUtensorMap* m, int c0, int c1, uint32_t bar) {
    asm volatile("cp.async.bulk.tensor.2d.shared::cluster.global.mbarrier::complete_tx::bytes [%0], [%1, {%3, %4}], [%2];"
                 ::"r"(dst), "l"(m), "r"(bar), "r"(c0), "r"(c1) : "memory");
}
DEVI void tma2d_prefetch(const CUtensorMap* m, int c0, int c1) {
    asm volatile("cp.async.bulk.prefetch.tensor.2d.L2.global [%0, {%1, %2}];" ::"l"(m), "r"(c0), "r"(c1) : "memory");
}
DEVI void tma2d_store(const CUtensorMap* m, uint32_t src, int c0, int c1) {
    asm volatile("cp.async.bulk.tensor.2d.global.shared::cta.bulk_group [%0, {%2, %3}], [%1];"
                 ::"l"(m), "r"(src), "r"(c0), "r"(c1) : "memory");
}
DEVI uint64_t mkdesc(uint32_t addr, uint32_t lbo, uint32_t sbo, uint32_t swz) {
    return (uint64_t)((addr & 0x3FFFF) >> 4) | ((uint64_t)(lbo >> 4) << 16) | ((uint64_t)(sbo >> 4) << 32) | ((uint64_t)swz << 62);
}
DEVI uint64_t desc_at(uint32_t db, uint32_t off, uint32_t lbo, uint32_t sbo, uint32_t swz) {
    const uint32_t lo = db + ((off >> 4) | ((lbo >> 4) << 16));
    const uint32_t hi = (sbo >> 4) | (swz << 30);
    uint64_t d; asm("mov.b64 %0, {%1, %2};" : "=l"(d) : "r"(lo), "r"(hi)); return d;
}
#define WG_FENCE() asm volatile("wgmma.fence.sync.aligned;" ::: "memory")
#define WG_COMMIT() asm volatile("wgmma.commit_group.sync.aligned;" ::: "memory")
#define WG_WAIT(n) asm volatile("wgmma.wait_group.sync.aligned " #n ";" ::: "memory")

template <int N> DEVI void acc_fence(float* d) {
#pragma unroll
    for (int i = 0; i < N; i++) asm volatile("" : "+f"(d[i])::"memory");
}
DEVI uint32_t pack_bf16(float lo, float hi) {
    uint32_t r; asm("cvt.rn.bf16x2.f32 %0, %1, %2;" : "=r"(r) : "f"(hi), "f"(lo)); return r;
}
DEVI uint32_t movtrans(uint32_t a) {
    uint32_t r; asm volatile("movmatrix.sync.aligned.m8n8.trans.b16 %0, %1;" : "=r"(r) : "r"(a)); return r;
}
DEVI void ldsm4(uint32_t* r, uint32_t addr) {
    asm volatile("ldmatrix.sync.aligned.m8n8.x4.shared.b16 {%0,%1,%2,%3}, [%4];"
                 : "=r"(r[0]), "=r"(r[1]), "=r"(r[2]), "=r"(r[3]) : "r"(addr) : "memory");
}
DEVI void ldsm4t(uint32_t* r, uint32_t addr) {
    asm volatile("ldmatrix.sync.aligned.m8n8.x4.trans.shared.b16 {%0,%1,%2,%3}, [%4];"
                 : "=r"(r[0]), "=r"(r[1]), "=r"(r[2]), "=r"(r[3]) : "r"(addr) : "memory");
}
DEVI void ldsm4_if(bool c, uint32_t* r, uint32_t addr) {
    asm volatile("{\n.reg .pred p;\nsetp.ne.u32 p, %5, 0;\nmov.u32 %0, 0;\nmov.u32 %1, 0;\nmov.u32 %2, 0;\nmov.u32 %3, 0;\n"
                 "@p ldmatrix.sync.aligned.m8n8.x4.shared.b16 {%0,%1,%2,%3}, [%4];\n}"
                 : "=&r"(r[0]), "=&r"(r[1]), "=&r"(r[2]), "=&r"(r[3]) : "r"(addr), "r"((uint32_t)c) : "memory");
}
DEVI void ldsm4_upd(bool c, uint32_t* r, uint32_t addr) {
    asm volatile("{\n.reg .pred p;\nsetp.ne.u32 p, %5, 0;\n@p ldmatrix.sync.aligned.m8n8.x4.shared.b16 {%0,%1,%2,%3}, [%4];\n}"
                 : "+r"(r[0]), "+r"(r[1]), "+r"(r[2]), "+r"(r[3]) : "r"(addr), "r"((uint32_t)c) : "memory");
}
DEVI void stsm2_sel(bool trans, uint32_t addr, uint32_t a, uint32_t b) {
    asm volatile("{\n.reg .pred p;\nsetp.ne.u32 p, %3, 0;\n@p stmatrix.sync.aligned.m8n8.x2.trans.shared.b16 [%0], {%1,%2};\n"
                 "@!p stmatrix.sync.aligned.m8n8.x2.shared.b16 [%0], {%1,%2};\n}" ::"r"(addr), "r"(a), "r"(b), "r"((uint32_t)trans) : "memory");
}
DEVI void hmma(float* d, uint32_t a0, uint32_t a1, uint32_t a2, uint32_t a3, uint32_t b0, uint32_t b1) {
    asm volatile("mma.sync.aligned.m16n8k16.row.col.f32.bf16.bf16.f32 {%0,%1,%2,%3}, {%4,%5,%6,%7}, {%8,%9}, {%0,%1,%2,%3};"
                 : "+f"(d[0]), "+f"(d[1]), "+f"(d[2]), "+f"(d[3])
                 : "r"(a0), "r"(a1), "r"(a2), "r"(a3), "r"(b0), "r"(b1));
}
DEVI void hmma8(float* d, uint32_t a0, uint32_t a1, uint32_t b0) {
    asm volatile("mma.sync.aligned.m16n8k8.row.col.f32.bf16.bf16.f32 {%0,%1,%2,%3}, {%4,%5}, {%6}, {%0,%1,%2,%3};"
                 : "+f"(d[0]), "+f"(d[1]), "+f"(d[2]), "+f"(d[3]) : "r"(a0), "r"(a1), "r"(b0));
}
DEVI uint4 lds128(uint32_t a) {
    uint4 v; asm volatile("ld.shared.v4.b32 {%0,%1,%2,%3}, [%4];" : "=r"(v.x), "=r"(v.y), "=r"(v.z), "=r"(v.w) : "r"(a) : "memory"); return v;
}
DEVI uint2 lds64(uint32_t a) {
    uint2 v; asm volatile("ld.shared.v2.b32 {%0,%1}, [%2];" : "=r"(v.x), "=r"(v.y) : "r"(a) : "memory"); return v;
}
DEVI float2 lds64f(uint32_t a) {
    float2 v; asm volatile("ld.shared.v2.f32 {%0,%1}, [%2];" : "=f"(v.x), "=f"(v.y) : "r"(a) : "memory"); return v;
}
DEVI void sts128(uint32_t a, uint32_t x, uint32_t y, uint32_t z, uint32_t w) {
    asm volatile("st.shared.v4.b32 [%0], {%1,%2,%3,%4};" ::"r"(a), "r"(x), "r"(y), "r"(z), "r"(w) : "memory");
}
DEVI void sts64(uint32_t a, uint32_t x, uint32_t y) {
    asm volatile("st.shared.v2.b32 [%0], {%1,%2};" ::"r"(a), "r"(x), "r"(y) : "memory");
}
DEVI void sts32(uint32_t a, uint32_t x) { asm volatile("st.shared.b32 [%0], %1;" ::"r"(a), "r"(x) : "memory"); }
DEVI void st_async64(uint32_t a, uint32_t x, uint32_t y, uint32_t bar) {
    asm volatile("st.async.weak.shared::cluster.mbarrier::complete_tx::bytes.v2.b32 [%0], {%1,%2}, [%3];"
                 ::"r"(a), "r"(x), "r"(y), "r"(bar) : "memory");
}
DEVI void st_async128(uint32_t a, uint32_t x, uint32_t y, uint32_t z, uint32_t w, uint32_t bar) {
    asm volatile("st.async.weak.shared::cluster.mbarrier::complete_tx::bytes.v4.b32 [%0], {%1,%2,%3,%4}, [%5];"
                 ::"r"(a), "r"(x), "r"(y), "r"(z), "r"(w), "r"(bar) : "memory");
}
DEVI uint4 ld_relaxed128(const void* p) {
    uint4 v; asm volatile("ld.relaxed.gpu.global.v4.b32 {%0,%1,%2,%3}, [%4];" : "=r"(v.x), "=r"(v.y), "=r"(v.z), "=r"(v.w) : "l"(p) : "memory"); return v;
}
DEVI void st_relaxed128(void* p, uint32_t x, uint32_t y, uint32_t z, uint32_t w) {
    asm volatile("st.relaxed.gpu.global.v4.b32 [%0], {%1,%2,%3,%4};" ::"l"(p), "r"(x), "r"(y), "r"(z), "r"(w) : "memory");
}
DEVI void st_relaxed64(void* p, uint32_t x, uint32_t y) {
    asm volatile("st.relaxed.gpu.global.v2.b32 [%0], {%1,%2};" ::"l"(p), "r"(x), "r"(y) : "memory");
}
DEVI void st_relaxed_b64(void* p, uint32_t x, uint32_t y) {
    asm volatile("{\n.reg .b64 v;\nmov.b64 v, {%1,%2};\nst.relaxed.gpu.global.b64 [%0], v;\n}" ::"l"(p), "r"(x), "r"(y) : "memory");
}
DEVI void st_relaxed_b128(void* p, uint32_t x, uint32_t y, uint32_t z, uint32_t w) {
    asm volatile("{\n.reg .b64 a, b;\n.reg .b128 v;\nmov.b64 a, {%1,%2};\nmov.b64 b, {%3,%4};\nmov.b128 v, {a, b};\n"
                 "st.relaxed.gpu.global.b128 [%0], v;\n}" ::"l"(p), "r"(x), "r"(y), "r"(z), "r"(w) : "memory");
}
template <int LUT> DEVI uint32_t lop3(uint32_t a, uint32_t b, uint32_t c) {
    uint32_t r; asm("lop3.b32 %0, %1, %2, %3, %4;" : "=r"(r) : "r"(a), "r"(b), "r"(c), "n"(LUT)); return r;
}
DEVI float rcp_approx(float x) { float r; asm("rcp.approx.ftz.f32 %0, %1;" : "=f"(r) : "f"(x)); return r; }
DEVI uint2 ld_relaxed64(const void* p) {
    uint2 v; asm volatile("{\n.reg .b64 a;\nld.relaxed.gpu.global.b64 a, [%2];\nmov.b64 {%0,%1}, a;\n}" : "=r"(v.x), "=r"(v.y) : "l"(p) : "memory"); return v;
}
DEVI uint4 ld_relaxed_2xb64(const void* p) {
    uint4 v; asm volatile("{\n.reg .b64 a, b;\nld.relaxed.gpu.global.v2.b64 {a, b}, [%4];\nmov.b64 {%0,%1}, a;\nmov.b64 {%2,%3}, b;\n}"
                          : "=r"(v.x), "=r"(v.y), "=r"(v.z), "=r"(v.w) : "l"(p) : "memory"); return v;
}
DEVI void st_relaxed32(void* p, uint32_t x) {
    asm volatile("st.relaxed.gpu.global.b32 [%0], %1;" ::"l"(p), "r"(x) : "memory");
}
DEVI uint32_t ld_acquire32(const void* p) {
    uint32_t v; asm volatile("ld.acquire.gpu.global.b32 %0, [%1];" : "=r"(v) : "l"(p) : "memory"); return v;
}
DEVI uint32_t ld_relaxed32(const void* p) {
    uint32_t v; asm volatile("ld.relaxed.gpu.global.b32 %0, [%1];" : "=r"(v) : "l"(p) : "memory"); return v;
}
DEVI void fence_gpu() { asm volatile("fence.acq_rel.gpu;" ::: "memory"); }
DEVI void red_add_relaxed(unsigned* p, unsigned v) {
    asm volatile("red.relaxed.gpu.global.add.u32 [%0], %1;" ::"l"(p), "r"(v) : "memory");
}
DEVI float ex2(float x) { float r; asm("ex2.approx.ftz.f32 %0, %1;" : "=f"(r) : "f"(x)); return r; }
DEVI int lane_now() { int l; asm volatile("mov.u32 %0, %%laneid;" : "=r"(l)); return l; }
DEVI uint32_t ctaid_now() { uint32_t l; asm volatile("mov.u32 %0, %%ctaid.x;" : "=r"(l)); return l; }
DEVI uint32_t ctaidy_now() { uint32_t l; asm volatile("mov.u32 %0, %%ctaid.y;" : "=r"(l)); return l; }
DEVI uint32_t crank_now() { uint32_t l; asm volatile("mov.u32 %0, %%cluster_ctarank;" : "=r"(l)); return l; }
DEVI uint32_t clk32() { uint32_t c; asm volatile("mov.u32 %0, %%clock;" : "=r"(c)::"memory"); return c; }

DEVI void wait_until(uint32_t t0, uint32_t n) {
    asm volatile("{\n.reg .pred p;\n.reg .u32 b;\nLW:\nmov.u32 b, %%clock;\nsub.u32 b, b, %0;\n"
                 "setp.lt.u32 p, b, %1;\n@p bra.uni LW;\n}" ::"r"(t0), "r"(n) : "memory");
}
DEVI void wait_signed(uint32_t t) {
    asm volatile("{\n.reg .pred p;\n.reg .s32 b;\nLW:\nmov.u32 b, %%clock;\nsub.s32 b, b, %0;\n"
                 "setp.lt.s32 p, b, 0;\n@p bra.uni LW;\n}" ::"r"(t) : "memory");
}
DEVI uint32_t gtime32() { uint32_t t; asm volatile("mov.u32 %0, %%globaltimer_lo;" : "=r"(t)::"memory"); return t; }
DEVI void wait_gtime(uint32_t t) {
    asm volatile("{\n.reg .pred p;\n.reg .s32 b;\nLW:\nmov.u32 b, %%globaltimer_lo;\nsub.s32 b, b, %0;\n"
                 "setp.lt.s32 p, b, 0;\n@p bra.uni LW;\n}" ::"r"(t) : "memory");
}
DEVI void st_async32_w(uint32_t a, uint32_t x, uint32_t bar) {
    asm volatile("{\n.reg .pred p;\nelect.sync _|p, 0xffffffff;\n"
                 "@p st.async.weak.shared::cluster.mbarrier::complete_tx::bytes.b32 [%0], %1, [%2];\n}" ::"r"(a), "r"(x), "r"(bar) : "memory");
}
template <int ID> DEVI void sched_cut(uint32_t v) {
    asm volatile("{\n.reg .pred p;\nsetp.eq.u32 p, %0, %1;\n@p trap;\n}" ::"r"(v), "n"(0x70000000 + ID) : "memory");
}
DEVI uint32_t lds32(uint32_t a) { uint32_t v; asm volatile("ld.shared.b32 %0, [%1];" : "=r"(v) : "r"(a) : "memory"); return v; }
DEVI void tma3d_prefetch_w(const CUtensorMap* m, int c0, int c1, int c2) {
    asm volatile("{\n.reg .pred p;\nelect.sync _|p, 0xffffffff;\n@p cp.async.bulk.prefetch.tensor.3d.L2.global [%0, {%1, %2, %3}];\n}"
                 ::"l"(m), "r"(c0), "r"(c1), "r"(c2) : "memory");
}

DEVI void wg_ss8_first(float* d, uint64_t da, uint64_t db) {
    asm volatile("wgmma.mma_async.sync.aligned.m64n8k16.f32.bf16.bf16 {%0,%1,%2,%3}, %4, %5, 0, 1, 1, 1, 1;"
                 : "=f"(d[0]), "=f"(d[1]), "=f"(d[2]), "=f"(d[3]) : "l"(da), "l"(db));
}
DEVI void wg_ss8_zero(float* d, uint64_t da, uint64_t db) {
    asm volatile("wgmma.mma_async.sync.aligned.m64n8k16.f32.bf16.bf16 {%0,%1,%2,%3}, %4, %5, 0, 1, 1, 1, 1;"
                 : "+f"(d[0]), "+f"(d[1]), "+f"(d[2]), "+f"(d[3]) : "l"(da), "l"(db));
}
DEVI void wg_ss8(float* d, uint64_t da, uint64_t db) {
    asm volatile("wgmma.mma_async.sync.aligned.m64n8k16.f32.bf16.bf16 {%0,%1,%2,%3}, %4, %5, 1, 1, 1, 1, 1;"
                 : "+f"(d[0]), "+f"(d[1]), "+f"(d[2]), "+f"(d[3]) : "l"(da), "l"(db));
}
DEVI void wg_ss16_first(float* d, uint64_t da, uint64_t db) {
    asm volatile("wgmma.mma_async.sync.aligned.m64n16k16.f32.bf16.bf16 {%0,%1,%2,%3,%4,%5,%6,%7}, %8, %9, 0, 1, 1, 1, 1;"
                 : "=f"(d[0]), "=f"(d[1]), "=f"(d[2]), "=f"(d[3]), "=f"(d[4]), "=f"(d[5]), "=f"(d[6]), "=f"(d[7]) : "l"(da), "l"(db));
}
DEVI void wg_ss16(float* d, uint64_t da, uint64_t db) {
    asm volatile("wgmma.mma_async.sync.aligned.m64n16k16.f32.bf16.bf16 {%0,%1,%2,%3,%4,%5,%6,%7}, %8, %9, 1, 1, 1, 1, 1;"
                 : "+f"(d[0]), "+f"(d[1]), "+f"(d[2]), "+f"(d[3]), "+f"(d[4]), "+f"(d[5]), "+f"(d[6]), "+f"(d[7]) : "l"(da), "l"(db));
}
#define ACC16(c) c(d[0]), c(d[1]), c(d[2]), c(d[3]), c(d[4]), c(d[5]), c(d[6]), c(d[7]), \
                 c(d[8]), c(d[9]), c(d[10]), c(d[11]), c(d[12]), c(d[13]), c(d[14]), c(d[15])
#define R16 "{%0,%1,%2,%3,%4,%5,%6,%7,%8,%9,%10,%11,%12,%13,%14,%15}"
DEVI void wg_rs32_first(float* d, const uint32_t* a, uint64_t db) {
    asm volatile("wgmma.mma_async.sync.aligned.m64n32k16.f32.bf16.bf16 " R16 ", {%16,%17,%18,%19}, %20, 0, 1, 1, 0;"
                 : ACC16("=f") : "r"(a[0]), "r"(a[1]), "r"(a[2]), "r"(a[3]), "l"(db));
}
DEVI void wg_rs32(float* d, const uint32_t* a, uint64_t db) {
    asm volatile("wgmma.mma_async.sync.aligned.m64n32k16.f32.bf16.bf16 " R16 ", {%16,%17,%18,%19}, %20, 1, 1, 1, 0;"
                 : ACC16("+f") : "r"(a[0]), "r"(a[1]), "r"(a[2]), "r"(a[3]), "l"(db));
}
DEVI void wg_ss32(float* d, uint64_t da, uint64_t db) {
    asm volatile("wgmma.mma_async.sync.aligned.m64n32k16.f32.bf16.bf16 " R16 ", %16, %17, 1, 1, 1, 1, 0;"
                 : ACC16("+f") : "l"(da), "l"(db));
}
DEVI void wg_tail32(float* d, uint64_t da, uint64_t db) {
    asm volatile("wgmma.mma_async.sync.aligned.m64n32k16.f32.bf16.bf16 " R16 ", %16, %17, 1, 1, 1, 0, 1;"
                 : ACC16("+f") : "l"(da), "l"(db));
}

DEVI void wg_gemm256(float* d, uint64_t da, uint64_t db) {
    asm volatile("wgmma.mma_async.sync.aligned.m64n256k16.f32.bf16.bf16 "
                 "{%0,%1,%2,%3,%4,%5,%6,%7,%8,%9,%10,%11,%12,%13,%14,%15,%16,%17,%18,%19,%20,%21,%22,%23,%24,%25,%26,%27,%28,%29,%30,%31,%32,%33,%34,%35,%36,%37,%38,%39,%40,%41,%42,%43,%44,%45,%46,%47,%48,%49,%50,%51,%52,%53,%54,%55,%56,%57,%58,%59,%60,%61,%62,%63,%64,%65,%66,%67,%68,%69,%70,%71,%72,%73,%74,%75,%76,%77,%78,%79,%80,%81,%82,%83,%84,%85,%86,%87,%88,%89,%90,%91,%92,%93,%94,%95,%96,%97,%98,%99,%100,%101,%102,%103,%104,%105,%106,%107,%108,%109,%110,%111,%112,%113,%114,%115,%116,%117,%118,%119,%120,%121,%122,%123,%124,%125,%126,%127}, %128, %129, 1, 1, 1, 0, 1;"
                 : "+f"(d[0]), "+f"(d[1]), "+f"(d[2]), "+f"(d[3]), "+f"(d[4]), "+f"(d[5]), "+f"(d[6]), "+f"(d[7]), "+f"(d[8]), "+f"(d[9]), "+f"(d[10]), "+f"(d[11]), "+f"(d[12]), "+f"(d[13]), "+f"(d[14]), "+f"(d[15]), "+f"(d[16]), "+f"(d[17]), "+f"(d[18]), "+f"(d[19]), "+f"(d[20]), "+f"(d[21]), "+f"(d[22]), "+f"(d[23]), "+f"(d[24]), "+f"(d[25]), "+f"(d[26]), "+f"(d[27]), "+f"(d[28]), "+f"(d[29]), "+f"(d[30]), "+f"(d[31]), "+f"(d[32]), "+f"(d[33]), "+f"(d[34]), "+f"(d[35]), "+f"(d[36]), "+f"(d[37]), "+f"(d[38]), "+f"(d[39]), "+f"(d[40]), "+f"(d[41]), "+f"(d[42]), "+f"(d[43]), "+f"(d[44]), "+f"(d[45]), "+f"(d[46]), "+f"(d[47]), "+f"(d[48]), "+f"(d[49]), "+f"(d[50]), "+f"(d[51]), "+f"(d[52]), "+f"(d[53]), "+f"(d[54]), "+f"(d[55]), "+f"(d[56]), "+f"(d[57]), "+f"(d[58]), "+f"(d[59]), "+f"(d[60]), "+f"(d[61]), "+f"(d[62]), "+f"(d[63]), "+f"(d[64]), "+f"(d[65]), "+f"(d[66]), "+f"(d[67]), "+f"(d[68]), "+f"(d[69]), "+f"(d[70]), "+f"(d[71]), "+f"(d[72]), "+f"(d[73]), "+f"(d[74]), "+f"(d[75]), "+f"(d[76]), "+f"(d[77]), "+f"(d[78]), "+f"(d[79]), "+f"(d[80]), "+f"(d[81]), "+f"(d[82]), "+f"(d[83]), "+f"(d[84]), "+f"(d[85]), "+f"(d[86]), "+f"(d[87]), "+f"(d[88]), "+f"(d[89]), "+f"(d[90]), "+f"(d[91]), "+f"(d[92]), "+f"(d[93]), "+f"(d[94]), "+f"(d[95]), "+f"(d[96]), "+f"(d[97]), "+f"(d[98]), "+f"(d[99]), "+f"(d[100]), "+f"(d[101]), "+f"(d[102]), "+f"(d[103]), "+f"(d[104]), "+f"(d[105]), "+f"(d[106]), "+f"(d[107]), "+f"(d[108]), "+f"(d[109]), "+f"(d[110]), "+f"(d[111]), "+f"(d[112]), "+f"(d[113]), "+f"(d[114]), "+f"(d[115]), "+f"(d[116]), "+f"(d[117]), "+f"(d[118]), "+f"(d[119]), "+f"(d[120]), "+f"(d[121]), "+f"(d[122]), "+f"(d[123]), "+f"(d[124]), "+f"(d[125]), "+f"(d[126]), "+f"(d[127])
                 : "l"(da), "l"(db));
}
DEVI void wg_gemm128(float* d, uint64_t da, uint64_t db) {
    asm volatile("wgmma.mma_async.sync.aligned.m64n128k16.f32.bf16.bf16 "
                 "{%0,%1,%2,%3,%4,%5,%6,%7,%8,%9,%10,%11,%12,%13,%14,%15,%16,%17,%18,%19,%20,%21,%22,%23,%24,%25,%26,%27,%28,%29,%30,%31,%32,%33,%34,%35,%36,%37,%38,%39,%40,%41,%42,%43,%44,%45,%46,%47,%48,%49,%50,%51,%52,%53,%54,%55,%56,%57,%58,%59,%60,%61,%62,%63}, %64, %65, 1, 1, 1, 0, 1;"
                 : "+f"(d[0]), "+f"(d[1]), "+f"(d[2]), "+f"(d[3]), "+f"(d[4]), "+f"(d[5]), "+f"(d[6]), "+f"(d[7]), "+f"(d[8]), "+f"(d[9]), "+f"(d[10]), "+f"(d[11]), "+f"(d[12]), "+f"(d[13]), "+f"(d[14]), "+f"(d[15]), "+f"(d[16]), "+f"(d[17]), "+f"(d[18]), "+f"(d[19]), "+f"(d[20]), "+f"(d[21]), "+f"(d[22]), "+f"(d[23]), "+f"(d[24]), "+f"(d[25]), "+f"(d[26]), "+f"(d[27]), "+f"(d[28]), "+f"(d[29]), "+f"(d[30]), "+f"(d[31]), "+f"(d[32]), "+f"(d[33]), "+f"(d[34]), "+f"(d[35]), "+f"(d[36]), "+f"(d[37]), "+f"(d[38]), "+f"(d[39]), "+f"(d[40]), "+f"(d[41]), "+f"(d[42]), "+f"(d[43]), "+f"(d[44]), "+f"(d[45]), "+f"(d[46]), "+f"(d[47]), "+f"(d[48]), "+f"(d[49]), "+f"(d[50]), "+f"(d[51]), "+f"(d[52]), "+f"(d[53]), "+f"(d[54]), "+f"(d[55]), "+f"(d[56]), "+f"(d[57]), "+f"(d[58]), "+f"(d[59]), "+f"(d[60]), "+f"(d[61]), "+f"(d[62]), "+f"(d[63])
                 : "l"(da), "l"(db));
}
DEVI void wg_gemm64(float* d, uint64_t da, uint64_t db) {
    asm volatile("wgmma.mma_async.sync.aligned.m64n64k16.f32.bf16.bf16 "
                 "{%0,%1,%2,%3,%4,%5,%6,%7,%8,%9,%10,%11,%12,%13,%14,%15,%16,%17,%18,%19,%20,%21,%22,%23,%24,%25,%26,%27,%28,%29,%30,%31}, %32, %33, 1, 1, 1, 0, 1;"
                 : "+f"(d[0]), "+f"(d[1]), "+f"(d[2]), "+f"(d[3]), "+f"(d[4]), "+f"(d[5]), "+f"(d[6]), "+f"(d[7]), "+f"(d[8]), "+f"(d[9]), "+f"(d[10]), "+f"(d[11]), "+f"(d[12]), "+f"(d[13]), "+f"(d[14]), "+f"(d[15]), "+f"(d[16]), "+f"(d[17]), "+f"(d[18]), "+f"(d[19]), "+f"(d[20]), "+f"(d[21]), "+f"(d[22]), "+f"(d[23]), "+f"(d[24]), "+f"(d[25]), "+f"(d[26]), "+f"(d[27]), "+f"(d[28]), "+f"(d[29]), "+f"(d[30]), "+f"(d[31])
                 : "l"(da), "l"(db));
}

constexpr int NSEG = 64, NHEAD = 32, RCTAS = 96;

__device__ uint4 g_Qf[NSEG * NHEAD * 512];
__device__ uint4 g_Kf[NSEG * NHEAD * 512];
__device__ uint4 g_Vf[NSEG * NHEAD * 512];
__device__ uint4 g_Kmf[NSEG * NHEAD * 128];
__device__ uint4 g_Vmf[NSEG * NHEAD * 128];
__device__ bf16 g_oB[2048 * 4096];
#define EMPTY4 {~0u, ~0u, ~0u, ~0u}
#define E4 EMPTY4, EMPTY4, EMPTY4, EMPTY4
#define E16 E4, E4, E4, E4
#define E64 E16, E16, E16, E16
#define E256 E64, E64, E64, E64
#define E1024 E256, E256, E256, E256
#define E4096 E1024, E1024, E1024, E1024
constexpr int MSLOT = 1024 + 128;
__device__ __align__(128) uint4 g_memx[4 * MSLOT] = {E4096, E256, E256};
__device__ __align__(128) uint4 g_ox[4 * 4096] = {E4096, E4096, E4096, E4096};
__device__ unsigned g_epoch;
__device__ unsigned g_vote[64];
struct GState { unsigned claim[5][32], cqkv[32], cob[32], exits, pad[31], segdone[NSEG / 2][32], tail[2][32]; };
__device__ __align__(128) GState g_gs2[2];
#define RHEAD lds32(sb + rk::HEAD)
#define RT(i)
#define PT(i)
#define RTV(i0, i, v)

#define MAR_A 80
#define MAR_B 96
#define DECAY 8
#define DSHIFT 3
#define MRELAX 1
#define TOLA 88
#define TOL 104
#define ATTACK 16
#define RECOVER 450
#define RECOVER0 450
#define DUR_A0 2050
#define DUR_B0 1300
#define WARN_B_AT 40
#define STRESS(k) 0
#define P1_CUT 0
#define G_GO_AT 9
#define P1_CHK 8
#define MCAST 0
#define MC_RANK 2
#define P2_STYLE 1
#define OK0 20
#define LATE_X 0
#define FLUSH_AT 0
#define EARLY_X 0
#define PRE 3
#define CHK 8
#define F0B 4
#define XP_QK 38
#define XP_V 20
namespace rk {
constexpr uint32_t WSSG = 17 * 2048;
constexpr uint32_t WO = 0, WSS = 43 * 2048, XR = WSS + 2 * WSSG, XS = XR + 32768, MEM = XS + 8192,
                   XO = MEM + 16384, KX = XO + 4096, QM = XO + 8192, KM = QM + 1024,
                   SP = KM + 1024, RED = SP + 2560, BARS = RED + 3072, SMEM_BYTES = BARS + 640;
constexpr uint32_t B_MEM = BARS, B_F0 = BARS + 8, B_FA = BARS + 16, B_G = BARS + 32, B_XF = BARS + 64, B_XE = BARS + 96,
                    B_XCH = BARS + 208, B_PV = BARS + 216, B_O = BARS + 224,
                   B_WO = BARS + 240, B_F1 = BARS + 248, B_VM = BARS + 256, B_OE = BARS + 264, REDO = BARS + 272, B_XO = BARS + 288, B_XOE = BARS + 296, CTL = BARS + 304, B_RED = BARS + 384, B_ST = BARS + 400,
                   B_TL = BARS + 128, B_TR = BARS + 136, B_TF = BARS + 512, B_TJ = BARS + 576, EPOCH = BARS + 632, HEAD = BARS + 624, SMALL = BARS + 628;
__host__ __device__ constexpr bool is_ss(int k) { return (k & 3) == 0 || k == 2; }
__host__ __device__ constexpr int ss_idx(int k) { return k == 2 ? 16 : k >> 2; }
__host__ __device__ constexpr int reg_idx(int k) { return k - (k >> 2) - 1 - (k > 2 ? 1 : 0); }
}

template <int U, int I0 = 0, int I1 = 8>
DEVI void x_unit(float* xa, const uint32_t* w, uint32_t sb, uint32_t db0, uint32_t dbg) {
    if (I0 == 0) mbar_spin(sb + rk::B_XF + 8 * (U & 3), (U >> 2) & 1);
    WG_FENCE();
#pragma unroll
    for (int ii = I0; ii < I1; ii++) {
        const int i = 7 - ii, k = U * 8 + i;
        const uint64_t db = desc_at(db0, rk::XR + (U & 3) * 8192 + (i >> 2) * 4096 + (i & 3) * 32, 16, 1024, 1);
        if (rk::is_ss(k)) {
            wg_ss32(xa, desc_at(dbg, rk::WSS + rk::ss_idx(k) * 2048, 1024, 1024, 1), db);
        } else if (U == 0 && ii == 0) {
            wg_rs32_first(xa, &w[rk::reg_idx(k) * 4], db);
        } else {
            wg_rs32(xa, &w[rk::reg_idx(k) * 4], db);
        }
    }
    WG_COMMIT();
}
template <int U>
DEVI void x_release(uint32_t sb, int seg, int cw, const CUtensorMap* tmX) {
    if constexpr (U < 6) {
        mbar_arrive_w(sb + rk::B_XE + 8 * (U & 3));
        const int nseg = seg + (U >= 4 ? 1 : 0);
        if (cw == (U & 1) * 4 + (U >> 1) && nseg < NSEG) {
            mbar_spin(sb + rk::B_XE + 8 * (U & 3), (U & 2) ? seg & 1 : U >> 2);
            const uint32_t bar = sb + rk::B_XF + 8 * (U & 3);
            mbar_expect_tx_w(bar, 8192);
            tma3d_w(sb + rk::XR + (U & 3) * 8192, tmX, 0, nseg * 32, 2 * ((U + 4) & 7), bar);
        }
    }
}
template <int B0, int B1>
DEVI void p1_blocks(float* d0, float* d1, const uint32_t* w, const uint32_t* pre, uint32_t memaddr, uint32_t wsaddr) {
#pragma unroll
    for (int kk = 2 * B0; kk < 2 * B1; kk++) {
        uint32_t b[4], a[4];
        ldsm4t(b, memaddr + kk * 512);
        const int k = 2 * kk, ord = k <= 2 ? k / 2 : k / 4 + 1;
        const uint32_t* r0 = &w[rk::is_ss(k) ? 0 : rk::reg_idx(k) * 4];
        if (rk::is_ss(k)) {
            if (ord < PRE) r0 = &pre[ord * 4];
            else { ldsm4t(a, wsaddr + rk::ss_idx(k) * 2048); r0 = a; }
        }
        const uint32_t* r1 = &w[rk::reg_idx(k + 1) * 4];
        hmma(d1, r1[0], r1[1], r1[2], r1[3], b[2], b[3]);
        hmma(d0, r0[0], r0[1], r0[2], r0[3], b[0], b[1]);
    }
}
template <int U>
DEVI void x_run(float* xa, const uint32_t* w, uint32_t sb, uint32_t db0, uint32_t dbg, int seg, int cw, uint32_t t, const CUtensorMap* tmX) {
    if constexpr (U < 8) {
        constexpr bool pq = U == XP_QK / 8, pv = U == XP_V / 8;
        constexpr int cut = pq ? XP_QK % 8 : (pv ? XP_V % 8 : 0);
        const bool pause = (pq || pv) && (t == 2) == pv;
        if constexpr (cut == 0) {
            if (pause) {
                WG_WAIT(0);
                x_release<U - 1>(sb, seg, cw, tmX);
                mbar_spin(sb + rk::B_O, (seg - 1) & 1);
            }
            x_unit<U>(xa, w, sb, db0, dbg);
            WG_WAIT(1);
            if (!pause) x_release<U - 1>(sb, seg, cw, tmX);
        } else {
            x_unit<U, 0, cut>(xa, w, sb, db0, dbg);
            WG_WAIT(1);
            x_release<U - 1>(sb, seg, cw, tmX);
            if (pause) mbar_spin(sb + rk::B_O, (seg - 1) & 1);
            x_unit<U, cut, 8>(xa, w, sb, db0, dbg);
        }
        x_run<U + 1>(xa, w, sb, db0, dbg, seg, cw, t, tmX);
    } else {
        mbar_spin(sb + rk::B_XOE, (seg - 1) & 1);
        WG_WAIT(0);
        x_release<7>(sb, seg, cw, tmX);
    }
}
template <bool BIG>
DEVI bool piece_ok(uint32_t dst, uint32_t bytes, int lane) {
    const uint32_t ca = dst + lane * 32 + (lane >> 2) * 4, cl = ca + bytes - 1024;
    uint32_t m = __vimax3_u32(lds32(ca), lds32(ca + 1024), lds32(cl));
    if (BIG) m = max(m, __vimax3_u32(lds32(ca + 2048), lds32(cl - 1024), lds32(cl - 2048)));
    return m != ~0u;
}
template <bool BIG>
DEVI void refetch(uint32_t dst, const uint4* src, uint32_t bytes, uint32_t bar, uint32_t& ph, int lane) {
    uint32_t it = 0;
#pragma unroll 1
    while (true) {
        bulk_load_w(dst, src, bytes, bar);
        mbar_spin(bar, ph);
        ph ^= 1;
        if (__all_sync(0xffffffffu, piece_ok<BIG>(dst, bytes, lane))) break;
        if (++it > SPIN_LIMIT) __trap();
    }
}
template <int I0, int I1>
DEVI void p2_run(float* acc, uint32_t db0) {
#pragma unroll
    for (int i = I0; i < I1; i++) {
        const uint64_t da = desc_at(db0, rk::WO + i * 2048, 1024, 1024, 1), db = desc_at(db0, rk::MEM + i * 256, 128, 128, 0);
        if (i == 0) wg_ss8_first(acc, da, db); else wg_ss8(acc, da, db);
    }
}
DEVI void flush_segment(uint32_t sb, int s, uint32_t h, uint32_t t) {
    const uint32_t o = (s * NHEAD + h) * 512;
    fence_proxy_async();
    bulk_store_w(t < 2 ? g_Qf + o + t * 256 : g_Vf + o, sb + rk::XO, 4096);
    bulk_store_w(t < 2 ? g_Kf + o + t * 256 : g_Vf + o + 256, sb + rk::KX, 4096);
    bulk_store_w(t < 2 ? g_Kmf + (o >> 2) + t * 64 : g_Vmf + (o >> 2), sb + (t < 2 ? rk::KM : rk::QM), t < 2 ? 1024 : 2048);
    asm volatile("cp.async.bulk.commit_group;" ::: "memory");
}
DEVI uint32_t xo_addr(uint32_t sb, uint32_t t, int cw) {
    const int ln = lane_now();
    return __shfl_sync(0xffffffffu, sb + rk::XO + (t < 2 ? (cw >> 1) * 2048 + ((ln >> 4) * 8 + (ln & 7)) * 64
                       + ((((cw & 1) * 2 + ((ln >> 3) & 1)) ^ (ln >> 1)) & 3) * 16 : cw * 1024 + ln * 16), ln);
}
template <int V> struct IntC { static constexpr int value = V; };
template <int N, int I = 0, class F> DEVI void static_for(F&& f) {
    if constexpr (I < N) { f(IntC<I>{}); static_for<N, I + 1>(f); }
}
DEVI uint32_t slab_off(int lane, int wi) {
    return ((lane & 7) + ((lane >> 4) << 3)) * 128 + (((wi * 2 + ((lane >> 3) & 1)) ^ (lane & 7)) << 4);
}

DEVI void stsm4(uint32_t addr, uint32_t a, uint32_t b, uint32_t c, uint32_t d) {
    asm volatile("stmatrix.sync.aligned.m8n8.x4.shared.b16 [%0], {%1,%2,%3,%4};" ::"r"(addr), "r"(a), "r"(b), "r"(c), "r"(d) : "memory");
}
DEVI void tma2d_store_w(const CUtensorMap* m, uint32_t src, int c0, int c1) {
    asm volatile("{\n.reg .pred p;\nelect.sync _|p, 0xffffffff;\n"
                 "@p cp.async.bulk.tensor.2d.global.shared::cta.bulk_group [%0, {%2, %3}], [%1];\n}"
                 ::"l"(m), "r"(src), "r"(c0), "r"(c1) : "memory");
}

DEVI void attn_b_rows(uint32_t q, uint32_t k, uint32_t km, uint32_t v, uint32_t vm, int mt, int T0, int nT, int lane,
                      uint32_t tile, uint32_t boxb) {
    const int g8 = lane >> 2, c = lane & 3;
    const uint32_t sw = (g8 * 4 + (c ^ ((g8 >> 1) & 3))) * 16;
    float s[5][4];
#pragma unroll
    for (int n = 0; n < 5; n++) s[n][0] = s[n][1] = s[n][2] = s[n][3] = 0.f;
#pragma unroll 1
    for (int eg = 0; eg < 4; eg++) {
        const uint4 a0 = lds128(q + eg * 2048 + mt * 1024 + sw), a1 = lds128(q + eg * 2048 + mt * 1024 + 512 + sw);
#pragma unroll
        for (int n = 0; n < 5; n++) {
            const uint4 b = lds128(n < 4 ? k + eg * 2048 + n * 512 + sw : km + eg * 512 + sw);
            hmma(s[n], a0.x, a1.x, a0.y, a1.y, b.x, b.y);
            hmma(s[n], a0.z, a1.z, a0.w, a1.w, b.z, b.w);
        }
    }
    const int d = mt * 16 + g8 - 2 * c;
#pragma unroll
    for (int n = 0; n < 4; n++)
#pragma unroll
        for (int i = 0; i < 4; i++)
            if (n * 8 + (i & 1) - (i >> 1) * 8 > d) s[n][i] = -INFINITY;
    const float sc = 0.08838834764831845f * 1.4426950408889634f;
    uint32_t p[10];
#pragma unroll
    for (int r = 0; r < 2; r++) {
        float m = -INFINITY;
#pragma unroll
        for (int n = 0; n < 5; n++) m = fmaxf(m, fmaxf(s[n][2 * r], s[n][2 * r + 1]));
        m = fmaxf(m, __shfl_xor_sync(0xffffffffu, m, 1));
        m = fmaxf(m, __shfl_xor_sync(0xffffffffu, m, 2));
        m *= -sc;
        float t = 0.f;
#pragma unroll
        for (int n = 0; n < 5; n++) {
            s[n][2 * r] = ex2(fmaf(s[n][2 * r], sc, m)); s[n][2 * r + 1] = ex2(fmaf(s[n][2 * r + 1], sc, m));
            t += s[n][2 * r] + s[n][2 * r + 1];
        }
        t += __shfl_xor_sync(0xffffffffu, t, 1);
        t += __shfl_xor_sync(0xffffffffu, t, 2);
        t = __fdividef(1.f, t);
#pragma unroll
        for (int n = 0; n < 5; n++) p[2 * n + r] = pack_bf16(s[n][2 * r] * t, s[n][2 * r + 1] * t);
    }
    const uint32_t base = tile + (mt * 16 + (lane & 15)) * 128;
#pragma unroll 2
    for (int T = T0; T < T0 + nT; T++) {
        const uint4 v0 = lds128(v + T * 1024 + lane * 16), v1 = lds128(v + T * 1024 + 512 + lane * 16);
        float a0[4] = {0.f, 0.f, 0.f, 0.f}, a1[4] = {0.f, 0.f, 0.f, 0.f};
        hmma8(a0, p[8], p[9], lds32(vm + T * 256 + lane * 4)); hmma8(a1, p[8], p[9], lds32(vm + T * 256 + 128 + lane * 4));
        hmma(a0, p[0], p[1], p[2], p[3], v0.x, v0.z); hmma(a1, p[0], p[1], p[2], p[3], v0.y, v0.w);
        hmma(a0, p[4], p[5], p[6], p[7], v1.x, v1.z); hmma(a1, p[4], p[5], p[6], p[7], v1.y, v1.w);
        stsm4(base + (T >> 2) * boxb + ((((T & 3) * 2 + (lane >> 4)) ^ (lane & 7)) << 4),
              pack_bf16(a0[0], a0[1]), pack_bf16(a0[2], a0[3]), pack_bf16(a1[0], a1[1]), pack_bf16(a1[2], a1[3]));
    }
}
DEVI void bulk_piece_w(uint32_t dst, const void* src, uint32_t bytes, uint32_t bar) {
    asm volatile("{\n.reg .pred p;\nelect.sync _|p, 0xffffffff;\n"
                 "@p cp.async.bulk.shared::cluster.global.mbarrier::complete_tx::bytes [%0], [%1], %2, [%3];\n}"
                 ::"r"(dst), "l"(src), "r"(bytes), "r"(bar) : "memory");
}

__global__ void __cluster_dims__(3, 2, 1) __launch_bounds__(384, 1)
r_kernel(const __grid_constant__ CUtensorMap tmWq, const __grid_constant__ CUtensorMap tmWk,
         const __grid_constant__ CUtensorMap tmWv, const __grid_constant__ CUtensorMap tmWo,
         const __grid_constant__ CUtensorMap tmX, const __grid_constant__ CUtensorMap tmObS,
         const __grid_constant__ CUtensorMap tmObL, bf16* __restrict__ out, const bf16* __restrict__ mem0) {
    extern __shared__ __align__(1024) uint8_t smem_raw[];
    const uint32_t sb = smem_u32(smem_raw);
    if ((sb & 0xFFFFFF) != 1024) __trap();
    constexpr uint32_t db0 = 1024 >> 4;
    const int tid = threadIdx.x, lane = tid & 31;
    const int cw = __shfl_sync(0xffffffffu, tid >> 5, 0);
    const uint32_t t = blockIdx.x;

    uint32_t smid; asm("mov.u32 %0, %%smid;" : "=r"(smid));
    const bool spare = blockIdx.y >= NHEAD, small = gridDim.y > NHEAD && !spare && smid < 64 && (smid & 14) == 0;
    if (tid == 0) {
        for (int j = 0; j < 4; j++) {
            mbar_init(sb + rk::B_MEM + 8 * j, j == 0 ? 4 : 1); mbar_init(sb + rk::B_G + 8 * j, 1);
            mbar_init(sb + rk::B_XF + 8 * j, 1); mbar_init(sb + rk::B_XE + 8 * j, 8);
        }
        for (int j = 0; j < 12; j++) mbar_init(sb + rk::B_ST + 8 * j, 1);
        mbar_init(sb + rk::B_XCH, 1);
        mbar_init(sb + rk::B_VM, 8);
        sts128(sb + rk::REDO, 0, 0, 0, 0);
        mbar_init(sb + rk::B_F1, 1);
        mbar_init(sb + rk::B_XO, 8);
        mbar_init(sb + rk::B_XOE, 1);
        mbar_init(sb + rk::B_TL, 6);
        for (int j = 0; j < 3; j++) mbar_init(sb + rk::B_TR + 8 * j, 1);
        for (int j = 0; j < 10; j++) mbar_init(sb + rk::B_TF + 8 * j, 1);
        mbar_init(sb + rk::B_PV, 4);
        mbar_init(sb + rk::B_WO, 1);
        mbar_init(sb + rk::B_O, 4);
        mbar_init(sb + rk::B_OE, 4);
        mbar_init(sb + rk::B_RED, 1);
        mbar_init(sb + rk::B_RED + 8, 1);
        sts32(sb + rk::SMALL, small);
        uint32_t hd = blockIdx.y;
        if (spare) {
            unsigned it = 0, left, n;
            do {
                n = ld_acquire32(&g_vote[32]); left = ld_relaxed32(&g_vote[0]);
                if (++it > SPIN_LIMIT) __trap();
            } while (!left && n < 16);
            hd = left ? 2 * (left - 1) + (hd & 1) : ~0u;
        }
        sts32(sb + rk::HEAD, hd);
        asm volatile("fence.mbarrier_init.release.cluster;" ::: "memory");
        if (t == 2) mbar_expect_tx(sb + rk::B_XCH, 2560);
        mbar_expect_tx(sb + rk::B_RED, 1536);
        mbar_expect_tx(sb + rk::B_RED + 8, 1536);
    }
    __syncthreads();
    asm volatile("barrier.cluster.arrive.aligned;" ::: "memory");
    auto head = [&] { return __reduce_max_sync(0xffffffffu, lds32(sb + rk::HEAD)); };
    const bool first = tid == 0 && t == 0 && !(blockIdx.y & 1);
    if (small || spare) {
        asm volatile("barrier.cluster.wait.aligned;" ::: "memory");
        bool leave = head() == ~0u;
        if (small) {
            uint32_t f;
            asm volatile("ld.shared::cluster.b32 %0, [%1];" : "=r"(f) : "r"(mapa(sb + rk::SMALL, lane % 6)) : "memory");
            if (__all_sync(0xffffffffu, f)) {
                if (first) sts32(sb + rk::SMALL, atomicCAS(&g_vote[0], 0u, (blockIdx.y >> 1) + 1) == 0 ? 2 : 1);
                asm volatile("barrier.cluster.arrive.aligned;\nbarrier.cluster.wait.aligned;" ::: "memory");
                asm volatile("ld.shared::cluster.b32 %0, [%1];" : "=r"(f) : "r"(mapa(sb + rk::SMALL, 0)) : "memory");
                leave = f == 2;
                cluster_sync();
            }
        } else if (tid == 352 && t == 0 && !(blockIdx.y & 1)) {
            unsigned it = 0;
            while (ld_relaxed32(&g_vote[32]) < 16) { if (++it > SPIN_LIMIT) __trap(); }
            st_relaxed32(&g_vote[0], 0);
            st_relaxed32(&g_vote[32], 0);
        }
        if (first && small) { fence_gpu(); red_add_relaxed(&g_vote[32], 1); }
        if (__any_sync(0xffffffffu, leave)) return;
    } else if (first && gridDim.y > NHEAD) {
        red_add_relaxed(&g_vote[32], 1);
    }
    __syncwarp();
    const bool waited = small || spare;

    if (cw < 8) {
        asm volatile("setmaxnreg.inc.sync.aligned.u32 232;");
        const int g = cw >> 2, wi = cw & 3;
        const uint32_t dbg = db0 + g * (rk::WSSG >> 4);
        uint32_t w[188];
        float xa[16];
        {
            const uint32_t h = head();
            const CUtensorMap* tmW = t == 2 ? &tmWv : (g == 0 ? &tmWq : &tmWk);
            const int col = h * 128 + (t == 2 ? g : (int)t) * 64;
            const bool el = (wi == 0);
            const uint32_t stg = sb + rk::WO + g * 40960, stg5 = sb + (g ? rk::XO : rk::XS);
            const int k0 = (h & 1) * 128 + t * 43;
#define SLOT(i) ((i) % 6 == 5 ? stg5 : stg + ((i) % 6) * 8192)
            if (el) {
                for (int i = 0; i < 6; i++) {
                    mbar_expect_tx_w(sb + rk::B_ST + 8 * (g * 6 + i), 8192);
                    tma2d_w(SLOT(i), tmW, col, i * 64, sb + rk::B_ST + 8 * (g * 6 + i));
                }
                if (g == 0) {
                    for (int u = 0; u < 4; u++) {
                        mbar_expect_tx_w(sb + rk::B_XF + 8 * u, 8192);
                        tma3d_w(sb + rk::XR + u * 8192, &tmX, 0, 0, 2 * u, sb + rk::B_XF + 8 * u);
                    }
                }
            }
            if (G_GO_AT < 0) asm volatile("griddepcontrol.launch_dependents;" ::: "memory");
            if (cw == 0) PT(1);
            const uint32_t lo = slab_off(lane, wi);
            if (cw == 1) {
                mbar_expect_tx_w(sb + rk::B_WO, t < 2 ? 43 * 2048 : 42 * 2048);
                for (int j = 40; j < (t < 2 ? 43 : 42); j++) tma2d_w(sb + rk::WO + j * 2048, &tmWo, (h >> 1) * 64, (k0 + j) * 16, sb + rk::B_WO);
            }
            static_for<16>([&](auto I) {
                constexpr int i = I.value;
                mbar_wait(sb + rk::B_ST + 8 * (g * 6 + i % 6), (i / 6) & 1);
                if (cw == 0) PT(2 + i);
#pragma unroll
                for (int ks = 0; ks < 4; ks++) {
                    const int k = i * 4 + ks;
                    if (rk::is_ss(k)) {
                        const uint4 v = lds128(SLOT(i) + ks * 2048 + (tid & 127) * 16);
                        sts128(sb + rk::WSS + g * rk::WSSG + rk::ss_idx(k) * 2048 + (tid & 127) * 16, v.x, v.y, v.z, v.w);
                    } else {
                        ldsm4t(&w[rk::reg_idx(k) * 4], SLOT(i) + ks * 2048 + lo);
                    }
                }
                fence_proxy_async();
                bar_sync(2 + g, 128);
                if (el) {
                    if (i + 6 < 16) {
                        mbar_expect_tx_w(sb + rk::B_ST + 8 * (g * 6 + i % 6), 8192);
                        tma2d_w(SLOT(i), tmW, col, (i + 6) * 64, sb + rk::B_ST + 8 * (g * 6 + i % 6));
                    } else if (i % 6 < 5) {
                        for (int j = 0; j < 4; j++)
                            tma2d_w(SLOT(i) + j * 2048, &tmWo, (h >> 1) * 64, (k0 + (g * 5 + i % 6) * 4 + j) * 16, sb + rk::B_WO);
                    }
                }
                if (i == G_GO_AT) asm volatile("griddepcontrol.launch_dependents;" ::: "memory");
                if constexpr (i & 1) {
                    x_unit<i / 2>(xa, w, sb, db0, dbg);
                    WG_WAIT(0);
                    x_release<i / 2>(sb, 0, cw, &tmX);
                }
            });
#undef SLOT
            bar_sync(1, 256);
        }
        if (cw == 0) PT(18);
        if (!waited) asm volatile("barrier.cluster.wait.aligned;" ::: "memory");
        if (cw == 0) PT(19);

        const bool scorer = t < 2 && cw < 5;
        const uint32_t ko = (lane & 7) * 64 + (((lane >> 3) ^ (lane >> 1)) & 3) * 16;
        const uint32_t ma = __shfl_sync(0xffffffffu, sb + rk::MEM + lane * 16, lane);
        const uint32_t wa = __shfl_sync(0xffffffffu, sb + rk::WSS + g * rk::WSSG + slab_off(lane, wi), lane);
        const uint32_t qa = __shfl_sync(0xffffffffu, sb + rk::QM + ko, lane);
        const uint32_t sta = __shfl_sync(0xffffffffu, sb + rk::QM + (t < 2 ? (cw >> 1) * 512 + (ko ^ ((cw & 1) * 32)) : cw * 256 + lane * 16), lane);
        uint32_t xoa = xo_addr(sb, t, cw);
#pragma unroll 1
        for (int s = 0; s < NSEG; s++) {
            acc_fence<16>(xa);
            uint32_t p[8];
#pragma unroll
            for (int i = 0; i < 8; i++) p[i] = pack_bf16(xa[2 * i], xa[2 * i + 1]);
            if (t < 2) {
                stsm4t(xoa, p[0], p[1], p[2], p[3]);
                stsm4t(xoa + 1024, p[4], p[5], p[6], p[7]);
            } else {
                sts128(xoa, p[0], p[1], p[2], p[3]);
                sts128(xoa + 512, p[4], p[5], p[6], p[7]);
            }
            mbar_arrive_w(sb + rk::B_XO);
            {
                const uint32_t ph = s & 1;
                float d0[4], d1[4];
                if (cw == 0) RT(0);
                mbar_spin(sb + rk::B_XO, ph);
                if (s == NSEG - 1 && t < 2 && g == 0) { mbar_arrive_w(sb + rk::B_VM); break; }
#pragma unroll 1
                for (int pass = 0; pass < 2; pass++) {
                    uint32_t pre[PRE * 4 + 1];
#pragma unroll
                    for (int i = 0; i < PRE; i++) ldsm4t(&pre[i * 4], wa + (i == 0 ? 0 : (i == 1 ? 16 : i - 1)) * 2048);
                    mbar_spin(sb + rk::B_F0, ph);
                    if (cw == 0 && pass == 0) { RT(1); RTV(2, 2, clk32()); }
                    d0[0] = d0[1] = d0[2] = d0[3] = d1[0] = d1[1] = d1[2] = d1[3] = 0.f;
                    p1_blocks<0, F0B>(d0, d1, w, pre, ma, wa);
                    mbar_spin(sb + rk::B_F1, ph);
                    p1_blocks<F0B, CHK - 1>(d0, d1, w, pre, ma, wa);
                    const bool fine = __all_sync(0xffffffffu, lds32(sb + rk::REDO + ((ma >> 2) & 12)) == 2 * s);
                    p1_blocks<CHK - 1, CHK>(d0, d1, w, pre, ma, wa);
                    if (__builtin_expect(fine, 1)) break;
                    mbar_spin(sb + rk::B_MEM, ph);
                    if (!__any_sync(0xffffffffu, lds32(sb + rk::REDO + (CHK > 6 ? (ma >> 2) & 12 : 0)) & 1)) break;
                }
                p1_blocks<CHK, 16>(d0, d1, w, w, ma, wa);
                stsm2_sel(t < 2, sta, pack_bf16(d0[0] + d1[0], d0[1] + d1[1]), pack_bf16(d0[2] + d1[2], d0[3] + d1[3]));
                mbar_arrive_w(sb + rk::B_VM);
                if (s == NSEG - 1) break;
                uint32_t kx[8];
                ldsm4_if(g == 0, kx, qa + wi * 512 - (rk::QM - rk::KX));
                ldsm4_if(g == 0, kx + 4, qa + wi * 512 + 2048 - (rk::QM - rk::KX));
                bar_sync(1, 256);
                if (cw == 0) RT(3);
                if (scorer) {
                    uint32_t q0[4], q1[4];
                    ldsm4(q0, qa);
                    ldsm4(q1, qa + 512);
                    ldsm4_upd(g == 1, kx, qa + 1024);
                    ldsm4_upd(g == 1, kx + 4, qa + 1536);
                    float sa[4] = {0.f, 0.f, 0.f, 0.f}, sc[4] = {0.f, 0.f, 0.f, 0.f};
                    hmma8(sa, q0[0], q0[1], kx[0]); hmma8(sc, q0[0], q0[1], kx[1]);
                    hmma8(sa, q0[2], q0[3], kx[2]); hmma8(sc, q0[2], q0[3], kx[3]);
                    hmma8(sa, q1[0], q1[1], kx[4]); hmma8(sc, q1[0], q1[1], kx[5]);
                    hmma8(sa, q1[2], q1[3], kx[6]); hmma8(sc, q1[2], q1[3], kx[7]);
                    st_async64(mapa(sb + rk::SP + t * 1280 + cw * 256 + ((ma & 0x1f0) >> 1), 2 + 3 * (blockIdx.y & 1)), __float_as_uint(sa[0] + sc[2]),
                               __float_as_uint(sa[1] + sc[3]), mapa(sb + rk::B_XCH, 2 + 3 * (blockIdx.y & 1)));
                }
                if (cw >= 6) {
                    mbar_expect_tx_w(sb + rk::B_XF + 8 * (cw & 3), 8192);
                    tma3d_w(sb + rk::XR + (cw & 3) * 8192, &tmX, 0, (s + 1) * 32, 2 * (cw & 3), sb + rk::B_XF + 8 * (cw & 3));
                }
                if (cw == 0) RT(4);
            }
            const int seg = s + 1;
            if (t == 2) mbar_spin(sb + rk::B_PV, s & 1);
            x_unit<0>(xa, w, sb, db0, dbg);
            xoa = xo_addr(sb, t, cw);
            x_run<1>(xa, w, sb, db0, dbg, seg, cw, t, &tmX);
            if (cw == 0) RT(8);
        }
        {
            const int lane = lane_now();
            const uint32_t h = head();
            int tid2; asm volatile("mov.u32 %0, %%tid.x;" : "=r"(tid2));
            const int cw = __reduce_max_sync(0xffffffffu, tid2 >> 5), g = cw >> 2, wi = cw & 3;
            GState* gs = &g_gs2[__reduce_max_sync(0xffffffffu, lds32(sb + rk::EPOCH)) & 1];
            if (cw == 4) PT(23);
            if (g == 1) mbar_wait(sb + rk::B_TL, 0);
            if (cw == 4) PT(24);
            if (t < 2) {
                const int sg = 60 + 2 * g + t, sh = sg * NHEAD + h;
                const uint32_t in = sb + rk::WSS + g * 98304, tile = sb + (g ? rk::WSS + 90112 : rk::XR), bar = sb + rk::B_TJ + 8 * g;
                if (wi == 0) {
                    asm volatile("fence.proxy.async;" ::: "memory");
                    mbar_expect_tx_w(bar, 28672);
                    bulk_piece_w(in, g_Qf + sh * 512, 8192, bar);
                    bulk_piece_w(in + 8192, g_Kf + sh * 512, 8192, bar);
                    bulk_piece_w(in + 24576, g_Kmf + sh * 128, 2048, bar);
                    bulk_piece_w(in + 16384, g_Vf + sh * 512, 8192, bar);
                    bulk_piece_w(in + 26624, g_Vmf + sh * 128, 2048, bar);
                }
                mbar_wait(bar, 0);
                attn_b_rows(in, in + 8192, in + 24576, in + 16384, in + 26624, wi & 1, (wi >> 1) * 4, 4, lane, tile, 4096);
                if (cw == 4) PT(25);
                fence_proxy_async();
                bar_sync(2 + g, 128);
                if (wi == 0) {
                    tma2d_store_w(&tmObS, tile, h * 128, sg * 32);
                    tma2d_store_w(&tmObS, tile + 4096, h * 128 + 64, sg * 32);
                    asm volatile("cp.async.bulk.commit_group;" ::: "memory");
                    asm volatile("cp.async.bulk.wait_group 0;" ::: "memory");
                    asm volatile("fence.proxy.async.global;" ::: "memory");
                    fence_gpu();
                    red_add_relaxed(&gs->tail[g][lane], 1);
                    if (g) PT(26);
                }
            }
            if (g == 0) mbar_wait(sb + rk::B_TL, 0);
            const int row0 = 1920 + 64 * g, col0 = ((h & 1) * 128 + t * 43) * 16;
            const uint32_t rank = t + 3 * (h & 1);
            const uint32_t fbar = sb + rk::B_TF + g * 32, ring = rk::WSS + g * 49152;
            auto load = [&](int j) {
                mbar_expect_tx_w(fbar + 8 * j, j < 3 ? 24576 : 16384);
#pragma unroll 1
                for (int i = 0; i < (j < 3 ? 3 : 2); i++)
                    tma2d_w(sb + ring + (j & 1) * 24576 + i * 8192, &tmObL, col0 + (j * 3 + i) * 64, row0, fbar + 8 * j);
            };
            if (cw < 3) mbar_expect_tx_w(sb + rk::B_TR + cw * 8, 10240);
            if (wi == 1) {
                unsigned it = 0;
                while (__any_sync(0xffffffffu, ld_acquire32(&gs->tail[g ? lane & 1 : 0][0]) < 64)) { if (++it > SPIN_LIMIT) __trap(); }
                PT(27 + g);
                if (g) bar_arrive(6, 160);
                asm volatile("fence.proxy.async;" ::: "memory");
#pragma unroll 1
                for (int j = 0; j < 2; j++) load(j);
            }
            float acc[32];
#pragma unroll
            for (int i = 0; i < 32; i++) acc[i] = 0.f;
            auto run = [&](int j, auto K0, auto K1) {
                const uint32_t da = db0 + ((ring + (j & 1) * 24576) >> 4), dw = db0 + j * 1536;
                WG_FENCE();
#pragma unroll
                for (int k = K0.value; k < K1.value; k++)
                    wg_gemm64(acc, desc_at(da, (k >> 2) * 8192 + (k & 3) * 32, 16, 1024, 1), desc_at(dw, rk::WO + k * 2048, 1024, 1024, 1));
                WG_COMMIT();
                WG_WAIT(0);
            };
#pragma unroll 1
            for (int j = 0; j < 3; j++) {
                mbar_wait(fbar + 8 * j, 0);
                run(j, IntC<0>{}, IntC<12>{});
                bar_sync(2 + g, 128);
                if (wi == 1 && j < 2) load(j + 2);
            }
            mbar_wait(fbar + 24, 0);
            run(3, IntC<0>{}, IntC<6>{});
            if (t < 2) run(3, IntC<6>{}, IntC<7>{});
            if (g == 0) bar_sync(6, 160);
            acc_fence<32>(acc);
            if (wi == 0) PT(29 + g);
#pragma unroll
            for (int nh = 0; nh < 2; nh++) {
                const uint32_t blk = cw * 2 + nh, owner = blk % 6;
                if (owner != rank) {
                    const uint32_t ra = mapa(sb + rk::WSS + 98304 + (blk / 6) * 10240 + (rank > owner ? rank - 1 : rank) * 2048 + lane * 16, owner);
                    const uint32_t rb = mapa(sb + rk::B_TR + (blk / 6) * 8, owner);
#pragma unroll
                    for (int i = 0; i < 4; i++) {
                        const float* c = &acc[nh * 16 + i * 4];
                        st_async128(ra + i * 512, __float_as_uint(c[0]), __float_as_uint(c[1]), __float_as_uint(c[2]), __float_as_uint(c[3]), rb);
                    }
                }
            }
#pragma unroll
            for (int nh = 0; nh < 2; nh++) {
                const uint32_t blk = cw * 2 + nh;
                if (blk % 6 == rank) {
                    mbar_wait(sb + rk::B_TR + (blk / 6) * 8, 0);
                    const uint32_t in = sb + rk::WSS + 98304 + (blk / 6) * 10240 + lane * 16;
                    uint32_t* op = (uint32_t*)(out + (size_t)(row0 + wi * 16 + (lane >> 2)) * 2048 + 1024 + (h >> 1) * 64 + nh * 32) + (lane & 3);
#pragma unroll
                    for (int i = 0; i < 4; i++) {
                        float* c = &acc[nh * 16 + i * 4];
#pragma unroll
                        for (int r = 0; r < 5; r++) {
                            const uint4 u = lds128(in + r * 2048 + i * 512);
                            c[0] += __uint_as_float(u.x); c[1] += __uint_as_float(u.y); c[2] += __uint_as_float(u.z); c[3] += __uint_as_float(u.w);
                        }
                        op[i * 4] = pack_bf16(c[0], c[1]);
                        op[i * 4 + 8 * 1024] = pack_bf16(c[2], c[3]);
                    }
                }
            }
        }
        if (cw == 4) PT(31);
        cluster_sync();
        if (cw == 4) PT(22);
    } else {
        asm volatile("setmaxnreg.dec.sync.aligned.u32 40;");
        const int a = cw - 8, at = tid - 256;
        const int rho = head() * 3 + blockIdx.x;
        {
            const uint4* m = (const uint4*)(mem0 + (lane >> 2) * 1024 + a * 256) + (lane & 3);
            uint4 x[8];
#pragma unroll
            for (int i = 0; i < 8; i++) x[i] = __ldg(m + i * 4);
            const uint32_t da = sb + rk::MEM + (a * 256 + ((lane >> 1) & 3) * 8 + (lane >> 3) * 2 + (lane & 1)) * 16;
#pragma unroll
            for (int i = 0; i < 8; i++) stsm4t(da + i * 512, x[i].x, x[i].y, x[i].z, x[i].w);
        }
        const uint32_t epoch = __reduce_max_sync(0xffffffffu, ld_relaxed32(&g_epoch));
        const uint32_t v0 = epoch * (NSEG - 1);
        GState* gs = &g_gs2[epoch & 1];
        sts32(sb + rk::EPOCH, epoch);
        if (rho == 1) for (int i = at; i < (int)(sizeof(GState) / 4); i += 128) st_relaxed32((unsigned*)&g_gs2[(epoch & 1) ^ 1] + i, 0);
        if (a == 3 && rho < 24) tma3d_prefetch_w(&tmX, 0, (rho >> 3) * 32, 2 * (rho & 7));
        bar_sync(5, 128);
        mbar_arrive_w(sb + rk::B_MEM);
        if (a == 0) { mbar_arrive_w(sb + rk::B_F0); mbar_arrive_w(sb + rk::B_F1); }
        uint32_t gph = 0;
        uint32_t TA = __reduce_max_sync(0xffffffffu, gtime32()), TB = TA;
        sts128(sb + rk::CTL, DUR_A0, DUR_B0, MAR_A, MAR_B);
        sts128(sb + rk::CTL + 16, RECOVER, 0, 0, 0);
        if (!waited) asm volatile("barrier.cluster.wait.aligned;" ::: "memory");

#pragma unroll 1
        for (int s = 0; s < NSEG - 1; s++) {
            const int lane = lane_now();
            const uint32_t h = head(), t = ctaid_now();
            const uint32_t v = v0 + s;
            mbar_spin(sb + rk::B_XO, s & 1);
            mbar_spin(sb + rk::B_MEM, s & 1);
            uint32_t tO = gtime32();
            if (t < 2) mbar_spin(sb + rk::B_VM, s & 1);
            else {
                const uint32_t va = sb + rk::XO + a * 2048 + lane * 16;
                uint32_t* op = (uint32_t*)(g_ox + (v & 3) * 4096 + h * 128 + a * 32) + lane;
                const uint4 v00 = lds128(va), v10 = lds128(va + 1024);
                mbar_spin(sb + rk::B_XCH, s & 1);
                if (a == 0) RT(16);
                float e[10];
#pragma unroll
                for (int n = 0; n < 5; n++) {
                    const float2 u = lds64f(sb + rk::SP + n * 256 + lane * 8), v = lds64f(sb + rk::SP + 1280 + n * 256 + lane * 8);
                    e[2 * n] = u.x + v.x; e[2 * n + 1] = u.y + v.y;
                }
                float mx = fmaxf(fmaxf(fmaxf(e[0], e[1]), fmaxf(e[2], e[3])), fmaxf(fmaxf(e[4], e[5]), fmaxf(e[6], e[7])));
                mx = fmaxf(mx, fmaxf(e[8], e[9]));
                mx = fmaxf(mx, __shfl_xor_sync(0xffffffffu, mx, 1));
                mx = fmaxf(mx, __shfl_xor_sync(0xffffffffu, mx, 2));
                const float sc = 0.08838834764831845f * 1.4426950408889634f;
                const float nm = -mx * sc;
                float o0[4] = {0.f, 0.f, 0.f, 0.f}, o1[4] = {0.f, 0.f, 0.f, 0.f}, sm[4] = {0.f, 0.f, 0.f, 0.f};
#pragma unroll
                for (int i = 0; i < 4; i++) e[i] = ex2(fmaf(e[i], sc, nm));
                {
                    const uint32_t b0 = pack_bf16(e[0], e[1]), b1 = pack_bf16(e[2], e[3]);
                    hmma(o0, v00.x, v00.y, v00.z, v00.w, b0, b1);
                    hmma(o1, v10.x, v10.y, v10.z, v10.w, b0, b1);
                }
                float sum = (e[0] + e[1]) + (e[2] + e[3]);
                const uint4 v01 = lds128(va + 512), v11 = lds128(va + 1536);
#pragma unroll
                for (int i = 4; i < 7; i++) e[i] = ex2(fmaf(e[i], sc, nm));
                mbar_spin(sb + rk::B_VM, s & 1);
                uint32_t vm[4];
                ldsm4(vm, va + (rk::QM - rk::XO) - a * 1536);
#pragma unroll
                for (int i = 7; i < 10; i++) e[i] = ex2(fmaf(e[i], sc, nm));
                {
                    const uint32_t b0 = pack_bf16(e[4], e[5]), b1 = pack_bf16(e[6], e[7]), bm = pack_bf16(e[8], e[9]);
                    hmma(o0, v01.x, v01.y, v01.z, v01.w, b0, b1);
                    hmma(o1, v11.x, v11.y, v11.z, v11.w, b0, b1);
                    sum = ((sum + ((e[4] + e[5]) + (e[6] + e[7]))) + e[8]) + e[9];
                    const float hi = __uint_as_float(__float_as_uint(sum) & 0xffff0000u);
                    hmma8(o0, vm[0], vm[1], bm);
                    hmma8(o1, vm[2], vm[3], bm);
                    hmma8(sm, 0x3F803F80u, 0x3F803F80u, pack_bf16(sum - hi, hi));
                }
                const float i0 = rcp_approx(sm[0]), i1 = rcp_approx(sm[1]);
                st_relaxed32(op, pack_bf16(o0[0] * i0, o0[1] * i1));
                st_relaxed32(op + 32, pack_bf16(o0[2] * i0, o0[3] * i1));
                st_relaxed32(op + 64, pack_bf16(o1[0] * i0, o1[1] * i1));
                st_relaxed32(op + 96, pack_bf16(o1[2] * i0, o1[3] * i1));
                mbar_arrive_w(sb + rk::B_PV);
                if (a == 3) tO = gtime32();
            }
            if (a == 0) RT(17);
            uint32_t failA = 0;
            const uint32_t own = a == 0 ? 2 : a - 1;
            {
                const uint4* osrc = g_ox + (v & 3) * 4096 + (h & 1) * 2048 + t * 688;
                constexpr uint32_t b0 = OK0 * 256;
                const uint32_t b1 = (t < 2 ? 43 * 256 : 42 * 256) - b0;
                if (a == 0) {
                    wait_gtime(TA - STRESS(0));
                    bulk_load_w(sb + rk::MEM, osrc, b0, sb + rk::B_FA);
                    bulk_load_w(sb + rk::MEM + b0, osrc + (b0 >> 4), b1, sb + rk::B_FA + 8);
                    sched_cut<1>(h);
                    flush_segment(sb, s, h, t);
                    RT(10);
                }
                const uint32_t q = (b0 + b1) >> 2;
                if (s == 0) {
                    mbar_spin(sb + rk::B_WO, 0);
                    if (a == 1) PT(21);
                    mbar_spin(sb + rk::B_FA, 0);
                    mbar_spin(sb + rk::B_FA + 8, 0);
                    if (!__all_sync(0xffffffffu, piece_ok<false>(sb + rk::MEM + a * q, q, lane)))
                        refetch<false>(sb + rk::MEM + a * q, osrc + a * (q >> 4), q, sb + rk::B_G + 8 * a, gph, lane);
                    bar_sync(5, 128);
                }
                float acc[4];
                const uint32_t ra = __shfl_sync(0xffffffffu, mapa(sb + rk::RED + ((a & 1) * 6 + (h & 1) * 3 + t) * 256 + lane * 8, own), lane);
                const uint32_t rbar = __shfl_sync(0xffffffffu, mapa(sb + rk::B_RED + 8 * (a & 1), own), lane);
                const uint32_t rk3 = mapa(sb, 3) - mapa(sb, 0);
#pragma unroll 1
                while (true) {
                    mbar_spin(sb + rk::B_FA, s & 1);
                    if (a == 0 && !failA) RT(18);
                    WG_FENCE();
                    p2_run<0, OK0>(acc, db0);
                    WG_COMMIT();
                    mbar_spin(sb + rk::B_FA + 8, s & 1);
                    if (t < 2) { WG_FENCE(); p2_run<OK0, 43>(acc, db0); WG_COMMIT(); }
                    else { WG_FENCE(); p2_run<OK0, 42>(acc, db0); WG_COMMIT(); }
                    WG_WAIT(0);
                    acc_fence<4>(acc);
                    if (__builtin_expect(!__any_sync(0xffffffffu, acc[0] != acc[0]), 1)) break;
                    const int ln = lane_now();
                    bool ok = true;
#pragma unroll 1
                    for (int j = 0; j < 4; j++) ok &= piece_ok<false>(sb + rk::MEM + j * q, q, ln);
                    if (__all_sync(0xffffffffu, ok)) break;
                    bar_sync(5, 128);
                    refetch<false>(sb + rk::MEM + a * q, osrc + a * (q >> 4), q, sb + rk::B_G + 8 * a, gph, ln);
                    failA = 1;
                    if (a == 0) RTV(25, 25, 1);
                    bar_sync(5, 128);
                }
                st_async64(ra, __float_as_uint(acc[0]), __float_as_uint(acc[1]), rbar);
                st_async64(ra + rk3, __float_as_uint(acc[2]), __float_as_uint(acc[3]), rbar + rk3);
                mbar_arrive_w(sb + (EARLY_X ? rk::B_OE : rk::B_O));
            }
            if (a == 0) RT(6);
            if (own == t) {
                const uint32_t blk = (h >> 1) * 8 + a * 2 + (h & 1);
                uint32_t mo = __shfl_sync(0xffffffffu, (((v + 1) & 3) * MSLOT + blk * 8) * 4 + lane, lane);
                const uint32_t ra = sb + rk::RED + (a & 1) * 1536 + lane * 8;
                mbar_spin(sb + rk::B_RED + 8 * (a & 1), s & 1);
                const float2 p0 = lds64f(ra), p1 = lds64f(ra + 256), p2 = lds64f(ra + 512), p3 = lds64f(ra + 768), p4 = lds64f(ra + 1024), p5 = lds64f(ra + 1280);
                st_relaxed32((uint32_t*)g_memx + mo, pack_bf16(((p0.x + p1.x) + (p2.x + p3.x)) + (p4.x + p5.x), ((p0.y + p1.y) + (p2.y + p3.y)) + (p4.y + p5.y)));
                const uint32_t now = gtime32();
                RT(19);
                {
                    const uint4 rd = lds128(sb + rk::REDO);
                    const uint32_t tw = (now & ~3u) | ((rd.x | rd.y | rd.z | rd.w) & 1), ot = (tO & ~3u) | failA;
                    st_relaxed32_if(lane < 8, (uint32_t*)(g_memx + ((v + 1 + ((lane >> 1) & 2)) & 3) * MSLOT + 1024 + blk) + (lane & 3),
                                    (lane & 4) ? ~0u : ((lane & 1) ? ot : tw));
                }
                st_relaxed32((uint32_t*)(g_memx + ((v + 3) & 3) * MSLOT + blk * 8) + lane, ~0u);
                mbar_expect_tx_w(sb + rk::B_RED + 8 * (a & 1), 1536);
            }
            if (t == 2) {
                st_relaxed128(g_ox + ((v + 2) & 3) * 4096 + h * 128 + a * 32 + lane, ~0u, ~0u, ~0u, ~0u);
                if (a == 0) mbar_expect_tx_w(sb + rk::B_XCH, 2560);
            }
            {
                const uint4* msrc = g_memx + ((v + 1) & 3) * MSLOT;
                if (a == 0) {
                    asm volatile("cp.async.bulk.wait_group 0;" ::: "memory");
                    mbar_arrive_w(sb + rk::B_XOE);
                }
                if ((s & 1) && a == (t < 2 ? 3 : 1)) {
                    mbar_spin(sb + rk::B_XOE, 1);
                    asm volatile("fence.proxy.async.global;" ::: "memory");
                    fence_gpu();
                    red_add_relaxed(&gs->segdone[s >> 1][lane], 1);
                }
                const bool careful = s == 0 || failA;
                const uint32_t po = F0B == 4 ? a * 4096 : (a ? 2560 + a * 3584 : 0), pb = F0B == 4 ? 4096 : (a ? (a == 3 ? 3072 : 3584) : 6144);
                bool ok = false;
                if (careful) {
                    mbar_spin(sb + (EARLY_X ? rk::B_OE : rk::B_O), s & 1);
                    wait_until(clk32(), 600);
                } else {
                    if (a == 0) {
                        mbar_spin(sb + (EARLY_X ? rk::B_OE : rk::B_O), s & 1);
                        wait_gtime(TB - STRESS(1));
                        bulk_load_w(sb + rk::MEM, msrc, F0B * 1024, sb + rk::B_F0);
                        bulk_load_w(sb + rk::MEM + F0B * 1024, msrc + F0B * 64, 16384 - F0B * 1024, sb + rk::B_F1);
                        RT(11);
                    }
                    mbar_spin(sb + (a ? rk::B_F1 : rk::B_F0), (s + 1) & 1);
                    if (a == 1) RT(14);
                    ok = __all_sync(0xffffffffu, piece_ok<true>(sb + rk::MEM + po, pb, lane));
                }
                if (!ok) refetch<true>(sb + rk::MEM + po, msrc + (po >> 4), pb, sb + rk::B_G + 8 * a, gph, lane);
                sts32(sb + rk::REDO + a * 4, 2 * (s + 1) + (!ok && !careful));
                mbar_arrive_w(sb + rk::B_MEM);
                RTV(25, 27 + a, !ok);
                RTV(21, 21 + a, rtnow());
                if (a == 0) {
                    if (careful) { mbar_arrive_w(sb + rk::B_F0); mbar_spin(sb + rk::B_MEM, (s + 1) & 1); mbar_arrive_w(sb + rk::B_F1); }
                    const uint4* rp = msrc + 1024 + lane;
                    uint2 r0, r1, r2, r3;
                    uint32_t it = 0;
#pragma unroll 1
                    while (true) {
                        r0 = ld_relaxed64(rp); r1 = ld_relaxed64(rp + 32); r2 = ld_relaxed64(rp + 64); r3 = ld_relaxed64(rp + 96);
                        if (__all_sync(0xffffffffu, max(__vimax3_u32(r0.x, r1.x, r2.x), __vimax3_u32(r3.x, __vimax3_u32(r0.y, r1.y, r2.y), r3.y)) != ~0u)) break;
                        if (++it > SPIN_LIMIT) __trap();
                    }
                    const uint32_t W = TB + __reduce_max_sync(0xffffffffu, max(max((int)(r0.x - TB), (int)(r1.x - TB)), max((int)(r2.x - TB), (int)(r3.x - TB))));
                    const uint32_t V = TB + __reduce_max_sync(0xffffffffu, max(max((int)(r0.y - TB), (int)(r1.y - TB)), max((int)(r2.y - TB), (int)(r3.y - TB))));
                    const uint4 c0 = lds128(sb + rk::CTL), c1 = lds128(sb + rk::CTL + 16);
                    uint32_t durA = c0.x, durB = c0.y, marA = c0.z, marB = c0.w, rec = c1.x, base = c1.y;
                    const bool clean = c1.z;
                    const bool fB = __any_sync(0xffffffffu, (r0.x | r1.x | r2.x | r3.x) & 1), fA = __any_sync(0xffffffffu, (r0.y | r1.y | r2.y | r3.y) & 1);
                    const bool okA = s > 0 && (int)(TA - V) >= (int)marA - TOLA, okB = s > 0 && (int)(TB - W) >= (int)marB - TOL;
                    auto track = [&](uint32_t dur, int d) { return dur + (d > 0 ? min(d, s < 4 ? 96 : (int)ATTACK) : max(d, min(-(int)DECAY, d >> DSHIFT))); };
                    marB = clean && fB ? marB + 32 : max(marB - MRELAX, (uint32_t)MAR_B);
                    marA = okA && fA ? marA + 32 : max(marA - MRELAX, (uint32_t)MAR_A);
                    if (clean && !fB) durA = track(durA, (int)(V - base - durA));
                    if (okA && !fA) durB = track(durB, (int)(W - TA - durB));
                    if (!clean && !okA && s > 1) rec += 160;
                    base = okB ? TB : W + (s == 0 ? RECOVER0 : rec);
                    TA = __reduce_max_sync(0xffffffffu, base + durA + marA);
                    TB = __reduce_max_sync(0xffffffffu, TA + durB + marB);
                    sts128(sb + rk::CTL, durA, durB, marA, marB);
                    sts128(sb + rk::CTL + 16, rec, base, okB, 0);
                    RTV(25, 12, durA); RTV(25, 13, durB); RTV(25, 26, okA + 2 * okB + 10 * marA + 10000 * marB);
                }
            }
            if (a == 2 && rho < 8 && s + 3 < NSEG) tma3d_prefetch_w(&tmX, 0, (s + 3) * 32, 2 * rho);
        }
        if (a == 0) {
            mbar_spin(sb + rk::B_MEM, (NSEG - 1) & 1);
            mbar_spin(sb + rk::B_XO, (NSEG - 1) & 1);
            mbar_spin(sb + rk::B_VM, (NSEG - 1) & 1);
            flush_segment(sb, NSEG - 1, head(), t);
            asm volatile("cp.async.bulk.wait_group 0;" ::: "memory");
            asm volatile("fence.proxy.async.global;" ::: "memory");
            for (int r = 0; r < 6; r++) mbar_arrive_cluster_w(mapa(sb + rk::B_TL, r));
            red_add_relaxed(&gs->segdone[NSEG / 2 - 1][lane], 1);
        }
        cluster_sync();
    }
}

__device__ bf16 g_qkvA[2048 * 3072];
__device__ bf16 g_oA[2048 * 1024];

struct GMaps { CUtensorMap ax, qkv, oa, ob, out, wqkv, wo, bwo, bwom, bwos; };

namespace gk {
#define NBIG 11
#define HALF_FROM 27
#define NWIDE 1
#define NMED 14
constexpr uint32_t STAGE = 49152, NST = 3, STG = NST * STAGE, BARS = STG + 65536, SMEM_BYTES = BARS + 256;
constexpr uint32_t B_FULL = BARS, B_EMPTY = BARS + 24, B_SF = BARS + 48, B_SE = BARS + 56, B_TF = BARS + 64, B_TE = BARS + 80,
                   TASK = BARS + 96, B_NEXT = BARS + 104;
constexpr uint32_t T_DONE = 7;
}

DEVI uint32_t g_schedule(int lane, GState* gs) {
    unsigned it = 0;
    while (true) {
        const unsigned cA = ld_relaxed32(&gs->cqkv[lane]);
        const unsigned cB = ld_relaxed32(&gs->cob[lane]), sd = ld_relaxed32(&gs->segdone[lane][0]);
        const unsigned k12 = ld_relaxed32(&gs->claim[1][lane]);
        const unsigned k3 = ld_relaxed32(&gs->claim[3][lane]), k45 = ld_relaxed32(&gs->claim[4][lane]);
        const unsigned k0 = ld_relaxed32(&gs->claim[0][0]);
        const unsigned dA = __ballot_sync(0xffffffffu, cA >= (lane < 16 ? 12u : 16u)), dB = __ballot_sync(0xffffffffu, cB >= 16);
        const unsigned o12 = __ballot_sync(0xffffffffu, k12 < (lane < 16 ? 16u : 4u));
        const unsigned o3 = __ballot_sync(0xffffffffu, lane < 30 && k3 < (lane >= HALF_FROM ? 16u : 8u));
        const unsigned o45 = __ballot_sync(0xffffffffu, lane < 16 ? lane < NMED && k45 < (lane >= NBIG ? 8u : 4u) : lane < 46 - 2 * NMED && k45 < (lane < 16 + NWIDE ? 8u : 16u));
        const bool o0 = __any_sync(0xffffffffu, k0 < 192);
        if (!(o12 | o3 | o45) && !o0) return gk::T_DONE << 16;
        const unsigned r1 = o12 & 0xffff & dA & (dA << 1 | 1) & (dA << 2 | 3), r2 = (o12 & dA) >> 16;
        const unsigned r3 = o3 & __ballot_sync(0xffffffffu, sd >= RCTAS);
        const unsigned r4 = o45 & __ballot_sync(0xffffffffu, lane < 16 && ((dB >> (2 * lane)) & 3) == 3);
        const unsigned o5 = o45 >> 16, r5 = o5 & (dB >> (2 * NMED));
        int t; unsigned m; bool early = false;
        if (r3) { t = 3; m = r3; }
        else if (r5 && o3 == (1u << 29)) { t = 3; m = o3; early = true; }
        else if (r5) { t = 5; m = r5; }
        else if (r4) { t = 4; m = r4; }
        else if (r2) { t = 2; m = r2; }
        else if (r1) { t = 1; m = r1; }
        else if (o0) { t = 0; m = 1; }
        else if (!(o12 | (o45 & 0xffff))) {
            early = true;
            if (o3) { t = 3; m = o3; } else { t = 5; m = o5; }
        } else {
            if (++it > (1u << 22)) __trap();
            __nanosleep(100);
            continue;
        }
        const int grp = __ffs(m) - 1;
        const unsigned gsz = t == 0 ? 192 : (t == 1 ? 16 : t == 5 ? (grp < NWIDE ? 8 : 16) : (t == 3 ? (grp >= HALF_FROM ? 16 : 8) : (t == 4 && grp >= NBIG ? 8 : 4)));
        unsigned idx = 0;
        if (lane == 0) idx = atomicAdd(t == 2 ? &gs->claim[1][16 + grp] : (t == 5 ? &gs->claim[4][16 + grp] : &gs->claim[t][grp]), 1u);
        idx = __shfl_sync(0xffffffffu, idx, 0);
        if (idx >= gsz) continue;
        if (t == 0) return (idx / 12) << 8 | idx % 12;
        if (early) {
            const unsigned* p = t == 3 ? &gs->segdone[grp][0] : &gs->cob[2 * NMED + grp];
            while (__any_sync(0xffffffffu, ld_relaxed32(p) < (t == 3 ? RCTAS : 16u))) { if (++it > (1u << 23)) __trap(); }
        }
        fence_gpu();
        return (unsigned)t << 16 | (unsigned)grp << 8 | idx;
    }
}

struct Pipe {
    uint32_t st = 0, ph = 0;
    DEVI void next() { if (++st == gk::NST) { st = 0; ph ^= 1; } }
};

template <int N>
DEVI void g_gemm_big(uint32_t sb, Pipe& pp, int nk, int g, int wi, int lane, uint32_t& sph) {
    float acc[N / 2];
#pragma unroll
    for (int i = 0; i < N / 2; i++) acc[i] = 0.f;
    const uint32_t db0 = (sb & 0x3FFFF) >> 4;
    uint32_t prev = 0;
#pragma unroll 1
    for (int k = 0; k < nk; k++) {
        mbar_wait(sb + gk::B_FULL + 8 * pp.st, pp.ph);
        const uint32_t da = db0 + pp.st * (gk::STAGE >> 4) + g * 512, dbb = db0 + pp.st * (gk::STAGE >> 4);
        WG_FENCE();
#pragma unroll
        for (int i = 0; i < 4; i++) {
            if constexpr (N == 256) wg_gemm256(acc, desc_at(da, i * 32, 16, 1024, 1), desc_at(dbb, 16384 + i * 2048, 8192, 1024, 1));
            else wg_gemm128(acc, desc_at(da, i * 32, 16, 1024, 1), desc_at(dbb, 16384 + i * 2048, 8192, 1024, 1));
        }
        WG_COMMIT();
        WG_WAIT(1);
        if (k > 0) mbar_arrive_w(sb + gk::B_EMPTY + 8 * prev);
        prev = pp.st;
        pp.next();
    }
    WG_WAIT(0);
    acc_fence<N / 2>(acc);
    mbar_arrive_w(sb + gk::B_EMPTY + 8 * prev);
    mbar_wait(sb + gk::B_SE, sph ^ 1);
    const uint32_t row = wi * 16 + (lane & 15);
    const uint32_t base = sb + gk::STG + g * (N * 128) + row * 128;
#pragma unroll
    for (int j = 0; j < N / 16; j++) {
        const float* c = &acc[j * 8];
        stsm4(base + (j >> 2) * 8192 + ((((j & 3) * 2 + (lane >> 4)) ^ (lane & 7)) << 4),
              pack_bf16(c[0], c[1]), pack_bf16(c[2], c[3]), pack_bf16(c[4], c[5]), pack_bf16(c[6], c[7]));
    }
}

DEVI void g_gemm_small(uint32_t sb, Pipe& pp, bool wide, int g, int wi, int lane, uint32_t& sph) {
    float acc[32];
#pragma unroll
    for (int i = 0; i < 32; i++) acc[i] = 0.f;
    const uint32_t db0 = (sb & 0x3FFFF) >> 4;
    uint32_t prev = 0;
#pragma unroll 1
    for (int k = 0; k < 32; k++) {
        mbar_wait(sb + gk::B_FULL + 8 * pp.st, pp.ph);
        const uint32_t ds = db0 + pp.st * (gk::STAGE >> 4);
        if (wide) {
            WG_FENCE();
#pragma unroll
            for (int i = 0; i < 8; i++)
                wg_gemm64(acc, desc_at(ds, (i >> 2) * 8192 + (i & 3) * 32, 16, 1024, 1), desc_at(ds + g * 1024, 16384 + i * 2048, 8192, 1024, 1));
            WG_COMMIT();
        } else {
            WG_FENCE();
#pragma unroll
            for (int i = 0; i < 4; i++)
                wg_gemm64(acc, desc_at(ds + g * 512, i * 32, 16, 1024, 1), desc_at(ds + g * 512, 16384 + i * 2048, 8192, 1024, 1));
            WG_COMMIT();
        }
        WG_WAIT(1);
        if (k > 0) mbar_arrive_w(sb + gk::B_EMPTY + 8 * prev);
        prev = pp.st;
        pp.next();
    }
    WG_WAIT(0);
    acc_fence<32>(acc);
    mbar_arrive_w(sb + gk::B_EMPTY + 8 * prev);
    mbar_wait(sb + gk::B_SE, sph ^ 1);
    if (!wide) {
        const uint32_t xa = sb + gk::STG + 16384 + (wi * 32 + lane) * 16;
        if (g == 1) {
#pragma unroll
            for (int j = 0; j < 8; j++)
                sts128(xa + j * 2048, __float_as_uint(acc[4 * j]), __float_as_uint(acc[4 * j + 1]), __float_as_uint(acc[4 * j + 2]), __float_as_uint(acc[4 * j + 3]));
        }
        bar_sync(1, 256);
        if (g == 1) return;
#pragma unroll
        for (int j = 0; j < 8; j++) {
            const uint4 v = lds128(xa + j * 2048);
            acc[4 * j] += __uint_as_float(v.x); acc[4 * j + 1] += __uint_as_float(v.y);
            acc[4 * j + 2] += __uint_as_float(v.z); acc[4 * j + 3] += __uint_as_float(v.w);
        }
    }
    const uint32_t base = sb + gk::STG + g * 8192 + (wi * 16 + (lane & 15)) * 128;
#pragma unroll
    for (int j = 0; j < 4; j++) {
        const float* c = &acc[j * 8];
        stsm4(base + (((j * 2 + (lane >> 4)) ^ (lane & 7)) << 4),
              pack_bf16(c[0], c[1]), pack_bf16(c[2], c[3]), pack_bf16(c[4], c[5]), pack_bf16(c[6], c[7]));
    }
}

DEVI void g_attn_a(uint32_t sb, Pipe& pp, int qb, int cw, int lane, uint32_t& sph) {
    const int hh = cw >> 2, wq = cw & 3;
    const int g8 = lane >> 2, c = lane & 3;
    const float sc = 0.17677669529663687f * 1.4426950408889634f;
    uint32_t q[2][2][4];
    float o[2][4][4], mx[2][2], sum[2][2];
#pragma unroll
    for (int mt = 0; mt < 2; mt++) {
        mx[mt][0] = mx[mt][1] = -INFINITY; sum[mt][0] = sum[mt][1] = 0.f;
#pragma unroll
        for (int n = 0; n < 4; n++) o[mt][n][0] = o[mt][n][1] = o[mt][n][2] = o[mt][n][3] = 0.f;
    }
    const int j0 = qb >= 2 ? 0 : 2 - qb;
    const uint32_t st0 = pp.st;
    Pipe rel = pp;
    int waited = j0 + 1, released = j0;
    mbar_wait(sb + gk::B_FULL + 8 * pp.st, pp.ph);
#pragma unroll
    for (int mt = 0; mt < 2; mt++)
#pragma unroll
        for (int ks = 0; ks < 2; ks++)
            ldsm4(q[mt][ks], sb + st0 * gk::STAGE + (wq * 32 + mt * 16 + (lane & 15)) * 128 + (((hh * 4 + ks * 2 + (lane >> 4)) ^ (lane & 7)) << 4));
    pp.next();
    const uint32_t ko = 16384 + (lane & 7) * 128 + (((hh * 4 + (lane >> 3)) ^ (lane & 7)) << 4);
    const uint32_t vo0 = 32768 + (lane & 15) * 128 + (((hh * 4 + (lane >> 4)) ^ (lane & 7)) << 4);
    const uint32_t vo1 = 32768 + (lane & 15) * 128 + (((hh * 4 + 2 + (lane >> 4)) ^ (lane & 7)) << 4);
#pragma unroll 1
    for (int ch = 0; ch < 3; ch++) {
        const int P0 = wq + 3 * ch;
        if (P0 + 2 < 4 * j0) continue;
#pragma unroll 1
        while (waited <= ((P0 + 2) >> 2)) { mbar_wait(sb + gk::B_FULL + 8 * pp.st, pp.ph); pp.next(); waited++; }
        uint32_t pb[3];
        float s[3][2][4][4];
        float nm[2][2] = {{mx[0][0], mx[0][1]}, {mx[1][0], mx[1][1]}};
#pragma unroll
        for (int p = 0; p < 3; p++) {
            const bool gone = P0 + p < 4 * j0;
            const int P = gone ? 4 * j0 : P0 + p;
            uint32_t st = st0 + (P >> 2) - j0;
            if (st >= gk::NST) st -= gk::NST;
            pb[p] = sb + st * gk::STAGE + (P & 3) * 4096;
#pragma unroll
            for (int n = 0; n < 4; n++) {
                uint32_t kf[4];
                ldsm4(kf, pb[p] + ko + n * 1024);
#pragma unroll
                for (int mt = 0; mt < 2; mt++) {
                    float* d = s[p][mt][n];
                    d[0] = d[1] = d[2] = d[3] = 0.f;
                    hmma(d, q[mt][0][0], q[mt][0][1], q[mt][0][2], q[mt][0][3], kf[0], kf[1]);
                    hmma(d, q[mt][1][0], q[mt][1][1], q[mt][1][2], q[mt][1][3], kf[2], kf[3]);
                }
            }
            if (p < 2 ? (gone || (p == 0 && ch == 0)) : ch == 2) {
#pragma unroll
                for (int mt = 0; mt < 2; mt++)
#pragma unroll
                    for (int n = 0; n < 4; n++)
#pragma unroll
                        for (int i = 0; i < 4; i++) {
                            const bool le = n * 8 + 2 * c + (i & 1) <= mt * 16 + g8 + (i >> 1) * 8;
                            if (p == 2 ? !le : (p == 1 || gone || le)) s[p][mt][n][i] = -INFINITY;
                        }
            }
#pragma unroll
            for (int mt = 0; mt < 2; mt++)
#pragma unroll
                for (int n = 0; n < 4; n++) {
                    nm[mt][0] = fmaxf(nm[mt][0], fmaxf(s[p][mt][n][0], s[p][mt][n][1]));
                    nm[mt][1] = fmaxf(nm[mt][1], fmaxf(s[p][mt][n][2], s[p][mt][n][3]));
                }
        }
        float off[2][2];
#pragma unroll
        for (int mt = 0; mt < 2; mt++)
#pragma unroll
            for (int r = 0; r < 2; r++) {
                float m = nm[mt][r];
                m = fmaxf(m, __shfl_xor_sync(0xffffffffu, m, 1));
                m = fmaxf(m, __shfl_xor_sync(0xffffffffu, m, 2));
                const float al = ex2((mx[mt][r] - m) * sc);
                mx[mt][r] = m; off[mt][r] = -m * sc;
                sum[mt][r] *= al;
#pragma unroll
                for (int n = 0; n < 4; n++) { o[mt][n][2 * r] *= al; o[mt][n][2 * r + 1] *= al; }
            }
        bar_sync(2 + cw, 64);
#pragma unroll
        for (int p = 0; p < 3; p++) {
#pragma unroll
            for (int kk = 0; kk < 2; kk++) {
                uint32_t v0[4], v1[4];
                ldsm4t(v0, pb[p] + vo0 + kk * 2048);
                ldsm4t(v1, pb[p] + vo1 + kk * 2048);
#pragma unroll
                for (int mt = 0; mt < 2; mt++) {
                    uint32_t a[4];
#pragma unroll
                    for (int n = 0; n < 2; n++) {
                        const float* d = s[p][mt][kk * 2 + n];
                        const float e0 = ex2(fmaf(d[0], sc, off[mt][0])), e1 = ex2(fmaf(d[1], sc, off[mt][0]));
                        const float e2 = ex2(fmaf(d[2], sc, off[mt][1])), e3 = ex2(fmaf(d[3], sc, off[mt][1]));
                        sum[mt][0] += e0 + e1; sum[mt][1] += e2 + e3;
                        a[n * 2] = pack_bf16(e0, e1); a[n * 2 + 1] = pack_bf16(e2, e3);
                    }
                    hmma(o[mt][0], a[0], a[1], a[2], a[3], v0[0], v0[1]);
                    hmma(o[mt][1], a[0], a[1], a[2], a[3], v0[2], v0[3]);
                    hmma(o[mt][2], a[0], a[1], a[2], a[3], v1[0], v1[1]);
                    hmma(o[mt][3], a[0], a[1], a[2], a[3], v1[2], v1[3]);
                }
            }
        }
        bar_arrive(2 + (cw ^ 4), 64);
        const int done = ch == 2 ? 3 : (P0 + 3) >> 2;
#pragma unroll 1
        while (released < done) { mbar_arrive_w(sb + gk::B_EMPTY + 8 * rel.st); rel.next(); released++; }
    }
    mbar_wait(sb + gk::B_SE, sph ^ 1);
#pragma unroll
    for (int mt = 0; mt < 2; mt++) {
        float i0 = sum[mt][0], i1 = sum[mt][1];
        i0 += __shfl_xor_sync(0xffffffffu, i0, 1); i1 += __shfl_xor_sync(0xffffffffu, i1, 1);
        i0 += __shfl_xor_sync(0xffffffffu, i0, 2); i1 += __shfl_xor_sync(0xffffffffu, i1, 2);
        i0 = __fdividef(1.f, i0); i1 = __fdividef(1.f, i1);
        const uint32_t base = sb + gk::STG + (wq * 32 + mt * 16 + (lane & 15)) * 128;
#pragma unroll
        for (int n = 0; n < 4; n += 2)
            stsm4(base + (((hh * 4 + n + (lane >> 4)) ^ (lane & 7)) << 4),
                  pack_bf16(o[mt][n][0] * i0, o[mt][n][1] * i0), pack_bf16(o[mt][n][2] * i1, o[mt][n][3] * i1),
                  pack_bf16(o[mt][n + 1][0] * i0, o[mt][n + 1][1] * i0), pack_bf16(o[mt][n + 1][2] * i1, o[mt][n + 1][3] * i1));
    }
}

DEVI void attn_b_job(int sh, int lane, uint32_t tile, uint32_t boxb, uint32_t bar, uint32_t parity) {
    const int g8 = lane >> 2, c = lane & 3;
    const int sw = g8 * 4 + (c ^ ((g8 >> 1) & 3));
    const uint4* Q = g_Qf + sh * 512 + sw; const uint4* K = g_Kf + sh * 512 + sw; const uint4* V = g_Vf + sh * 512 + lane;
    const uint4* Km = g_Kmf + sh * 128 + sw; const uint32_t* Vm = (const uint32_t*)(g_Vmf + sh * 128) + lane;
    float s0[3][4], s1[5][4];
#pragma unroll
    for (int n = 0; n < 3; n++) s0[n][0] = s0[n][1] = s0[n][2] = s0[n][3] = 0.f;
#pragma unroll
    for (int n = 0; n < 5; n++) s1[n][0] = s1[n][1] = s1[n][2] = s1[n][3] = 0.f;
    uint4 q[4][4], k[4][5];
#pragma unroll
    for (int eg = 0; eg < 4; eg++) {
#pragma unroll
        for (int n = 0; n < 4; n++) { q[eg][n] = __ldcg(Q + eg * 128 + n * 32); k[eg][n] = __ldcg(K + eg * 128 + n * 32); }
        k[eg][4] = __ldcg(Km + eg * 32);
    }
#pragma unroll
    for (int eg = 0; eg < 4; eg++) {
        const uint4* a = q[eg]; const uint4* b = k[eg];
#pragma unroll
        for (int n = 0; n < 5; n++) {
            if (n < 2 || n == 4) {
                float* d = s0[n == 4 ? 2 : n];
                hmma(d, a[0].x, a[1].x, a[0].y, a[1].y, b[n].x, b[n].y);
                hmma(d, a[0].z, a[1].z, a[0].w, a[1].w, b[n].z, b[n].w);
            }
            hmma(s1[n], a[2].x, a[3].x, a[2].y, a[3].y, b[n].x, b[n].y);
            hmma(s1[n], a[2].z, a[3].z, a[2].w, a[3].w, b[n].z, b[n].w);
        }
    }
    uint4 v0[8], v1[8]; uint2 vm[8];
#pragma unroll
    for (int T = 0; T < 8; T++) { v0[T] = __ldcg(V + T * 64); v1[T] = __ldcg(V + T * 64 + 32); vm[T] = make_uint2(__ldcg(Vm + T * 64), __ldcg(Vm + T * 64 + 32)); }
#pragma unroll
    for (int n = 0; n < 2; n++)
#pragma unroll
        for (int i = 0; i < 4; i++)
            if (n * 8 + 2 * c + (i & 1) > g8 + (i >> 1) * 8) { s0[n][i] = -INFINITY; s1[2 + n][i] = -INFINITY; }
    const float sc = 0.08838834764831845f * 1.4426950408889634f;
    uint32_t pa[6], pb[10];
#pragma unroll
    for (int r = 0; r < 2; r++) {
        float m0 = -INFINITY, m1 = -INFINITY;
#pragma unroll
        for (int n = 0; n < 3; n++) m0 = fmaxf(m0, fmaxf(s0[n][2 * r], s0[n][2 * r + 1]));
#pragma unroll
        for (int n = 0; n < 5; n++) m1 = fmaxf(m1, fmaxf(s1[n][2 * r], s1[n][2 * r + 1]));
        m0 = fmaxf(m0, __shfl_xor_sync(0xffffffffu, m0, 1)); m1 = fmaxf(m1, __shfl_xor_sync(0xffffffffu, m1, 1));
        m0 = fmaxf(m0, __shfl_xor_sync(0xffffffffu, m0, 2)); m1 = fmaxf(m1, __shfl_xor_sync(0xffffffffu, m1, 2));
        m0 *= -sc; m1 *= -sc;
        float t0 = 0.f, t1 = 0.f;
#pragma unroll
        for (int n = 0; n < 3; n++) {
            s0[n][2 * r] = ex2(fmaf(s0[n][2 * r], sc, m0)); s0[n][2 * r + 1] = ex2(fmaf(s0[n][2 * r + 1], sc, m0));
            t0 += s0[n][2 * r] + s0[n][2 * r + 1];
        }
#pragma unroll
        for (int n = 0; n < 5; n++) {
            s1[n][2 * r] = ex2(fmaf(s1[n][2 * r], sc, m1)); s1[n][2 * r + 1] = ex2(fmaf(s1[n][2 * r + 1], sc, m1));
            t1 += s1[n][2 * r] + s1[n][2 * r + 1];
        }
        t0 += __shfl_xor_sync(0xffffffffu, t0, 1); t1 += __shfl_xor_sync(0xffffffffu, t1, 1);
        t0 += __shfl_xor_sync(0xffffffffu, t0, 2); t1 += __shfl_xor_sync(0xffffffffu, t1, 2);
        t0 = __fdividef(1.f, t0); t1 = __fdividef(1.f, t1);
#pragma unroll
        for (int n = 0; n < 3; n++) pa[2 * n + r] = pack_bf16(s0[n][2 * r] * t0, s0[n][2 * r + 1] * t0);
#pragma unroll
        for (int n = 0; n < 5; n++) pb[2 * n + r] = pack_bf16(s1[n][2 * r] * t1, s1[n][2 * r + 1] * t1);
    }
    if (bar) mbar_wait(bar, parity);
    const uint32_t base = tile + (lane & 15) * 128;
#pragma unroll
    for (int T = 0; T < 8; T++) {
        float a0[4] = {0.f, 0.f, 0.f, 0.f}, a1[4] = {0.f, 0.f, 0.f, 0.f}, b0[4] = {0.f, 0.f, 0.f, 0.f}, b1[4] = {0.f, 0.f, 0.f, 0.f};
        hmma8(a0, pa[4], pa[5], vm[T].x); hmma8(a1, pa[4], pa[5], vm[T].y);
        hmma8(b0, pb[8], pb[9], vm[T].x); hmma8(b1, pb[8], pb[9], vm[T].y);
        hmma(a0, pa[0], pa[1], pa[2], pa[3], v0[T].x, v0[T].z); hmma(a1, pa[0], pa[1], pa[2], pa[3], v0[T].y, v0[T].w);
        hmma(b0, pb[0], pb[1], pb[2], pb[3], v0[T].x, v0[T].z); hmma(b1, pb[0], pb[1], pb[2], pb[3], v0[T].y, v0[T].w);
        hmma(b0, pb[4], pb[5], pb[6], pb[7], v1[T].x, v1[T].z); hmma(b1, pb[4], pb[5], pb[6], pb[7], v1[T].y, v1[T].w);
        const uint32_t ad = base + (T >> 2) * boxb + ((((T & 3) * 2 + (lane >> 4)) ^ (lane & 7)) << 4);
        stsm4(ad, pack_bf16(a0[0], a0[1]), pack_bf16(a0[2], a0[3]), pack_bf16(a1[0], a1[1]), pack_bf16(a1[2], a1[3]));
        stsm4(ad + 2048, pack_bf16(b0[0], b0[1]), pack_bf16(b0[2], b0[3]), pack_bf16(b1[0], b1[1]), pack_bf16(b1[2], b1[3]));
    }
}

__global__ void __launch_bounds__(384, 1) g_kernel(const __grid_constant__ GMaps mp) {
    extern __shared__ __align__(1024) uint8_t smem_raw[];
    const uint32_t sb = smem_u32(smem_raw);
    if (sb & 1023) __trap();
    const int tid = threadIdx.x, lane = tid & 31;
    const int cw = __shfl_sync(0xffffffffu, tid >> 5, 0);
    if (tid == 0) {
        for (int i = 0; i < 3; i++) { mbar_init(sb + gk::B_FULL + 8 * i, 1); mbar_init(sb + gk::B_EMPTY + 8 * i, 8); }
        mbar_init(sb + gk::B_SF, 8); mbar_init(sb + gk::B_SE, 1);
        for (int i = 0; i < 2; i++) { mbar_init(sb + gk::B_TF + 8 * i, 1); mbar_init(sb + gk::B_TE + 8 * i, 10); }
        mbar_init(sb + gk::B_NEXT, 1);
        fence_proxy_async();
    }
    __syncthreads();
    if (cw < 8) {
        asm volatile("setmaxnreg.inc.sync.aligned.u32 232;");
        const int g = cw >> 2, wi = cw & 3;
        Pipe pp;
        uint32_t sph = 0;
        if (g == 1) bar_arrive(2 + wi, 64);
#pragma unroll 1
        for (uint32_t n = 0;; n++) {
            mbar_wait(sb + gk::B_TF + 8 * (n & 1), (n >> 1) & 1);
            const uint32_t task = __shfl_sync(0xffffffffu, lds32(sb + gk::TASK + 4 * (n & 1)), 0);
            mbar_arrive_w(sb + gk::B_TE + 8 * (n & 1));
            const uint32_t ty = task >> 16, grp = (task >> 8) & 255, idx = task & 255;
            if (ty == gk::T_DONE) break;
            if (ty == 1) g_attn_a(sb, pp, grp, cw, lane, sph);
            else if (ty == 3) {
                const bool half = grp >= HALF_FROM;
                const int sg = half ? wi >> 1 : g, hd = half ? wi & 1 : wi;
                if (!half || g == 0)
                    attn_b_job((grp * 2 + sg) * NHEAD + idx * (half ? 2 : 4) + hd, lane, sb + gk::STG + hd * 16384 + sg * 4096, 8192, sb + gk::B_SE, sph ^ 1);
                else
                    mbar_wait(sb + gk::B_SE, sph ^ 1);
            }
            else if (ty == 5) g_gemm_small(sb, pp, grp < NWIDE, g, wi, lane, sph);
            else if (ty == 4 && grp >= NBIG) g_gemm_big<128>(sb, pp, 64, g, wi, lane, sph);
            else g_gemm_big<256>(sb, pp, ty == 4 ? 64 : 16, g, wi, lane, sph);
            fence_proxy_async();
            __syncwarp();
            mbar_arrive_w(sb + gk::B_SF);
            sph ^= 1;
        }
    } else {
        asm volatile("setmaxnreg.dec.sync.aligned.u32 40;");
        const uint32_t epoch = __shfl_sync(0xffffffffu, ld_relaxed32(&g_epoch), 0);
        GState* gs = &g_gs2[epoch & 1];
        if (cw == 8) {
            Pipe pp;
#pragma unroll 1
            for (uint32_t n = 0;; n++) {
                mbar_wait(sb + gk::B_TF + 8 * (n & 1), (n >> 1) & 1);
                const uint32_t task = __shfl_sync(0xffffffffu, lds32(sb + gk::TASK + 4 * (n & 1)), 0);
                mbar_arrive_w(sb + gk::B_TE + 8 * (n & 1));
                const uint32_t ty = task >> 16, grp = (task >> 8) & 255, idx = task & 255;
                if (ty == gk::T_DONE) break;
                asm volatile("fence.proxy.async.global;" ::: "memory");
                if (ty == 1 || ty == 3) mbar_arrive_w(sb + gk::B_NEXT);
                if (ty == 1) {
                    const int j0 = grp >= 2 ? 0 : 2 - grp;
#pragma unroll 1
                    for (int j = j0; j < 3; j++) {
                        mbar_wait(sb + gk::B_EMPTY + 8 * pp.st, pp.ph ^ 1);
                        const uint32_t stg = sb + pp.st * gk::STAGE, bar = sb + gk::B_FULL + 8 * pp.st;
                        const int r = ((int)grp - 2 + j) * 128;
                        mbar_expect_tx_w(bar, j == j0 ? 49152 : 32768);
                        if (j == j0) {
                            tma2d_w(stg, &mp.qkv, idx * 64, grp * 128, bar);
                            tma2d_w(stg + 8192, &mp.qkv, idx * 64, grp * 128 + 64, bar);
                        }
                        tma2d_w(stg + 16384, &mp.qkv, 1024 + idx * 64, r, bar);
                        tma2d_w(stg + 24576, &mp.qkv, 1024 + idx * 64, r + 64, bar);
                        tma2d_w(stg + 32768, &mp.qkv, 2048 + idx * 64, r, bar);
                        tma2d_w(stg + 40960, &mp.qkv, 2048 + idx * 64, r + 64, bar);
                        pp.next();
                    }
                } else if (ty == 5) {
                    const int r = (2 * NMED + grp) * 64;
                    const bool wide = grp < NWIDE;
#pragma unroll 1
                    for (int k = 0; k < 32; k++) {
                        if (k == 26) mbar_arrive_w(sb + gk::B_NEXT);
                        mbar_wait(sb + gk::B_EMPTY + 8 * pp.st, pp.ph ^ 1);
                        const uint32_t stg = sb + pp.st * gk::STAGE, bar = sb + gk::B_FULL + 8 * pp.st;
                        mbar_expect_tx_w(bar, wide ? 49152 : 32768);
                        tma2d_w(stg, &mp.ob, k * 128, r, bar);
                        tma2d_w(stg + 8192, &mp.ob, k * 128 + 64, r, bar);
                        tma2d_w(stg + 16384, &mp.bwos, idx * (wide ? 128 : 64), k * 128, bar);
                        if (wide) tma2d_w(stg + 32768, &mp.bwos, idx * 128 + 64, k * 128, bar);
                        pp.next();
                    }
                } else if (ty != 3) {
                    const CUtensorMap* ma = ty == 0 ? &mp.ax : (ty == 2 ? &mp.oa : &mp.ob);
                    const bool med = ty == 4 && grp >= NBIG;
                    const CUtensorMap* mb = ty == 0 ? &mp.wqkv : (ty == 2 ? &mp.wo : (med ? &mp.bwom : &mp.bwo));
                    const int nk = ty == 4 ? 64 : 16;
#pragma unroll 1
                    for (int k = 0; k < nk; k++) {
                        if (k == nk - (med ? 6 : 3)) mbar_arrive_w(sb + gk::B_NEXT);
                        mbar_wait(sb + gk::B_EMPTY + 8 * pp.st, pp.ph ^ 1);
                        const uint32_t stg = sb + pp.st * gk::STAGE, bar = sb + gk::B_FULL + 8 * pp.st;
                        mbar_expect_tx_w(bar, med ? 32768 : 49152);
                        tma2d_w(stg, ma, k * 64, grp * 128, bar);
                        tma2d_w(stg + 8192, ma, k * 64, grp * 128 + 64, bar);
                        tma3d_w(stg + 16384, mb, 0, k * 64, idx * (med ? 2 : 4), bar);
                        pp.next();
                    }
                }
            }
        } else if (cw == 9) {
            uint32_t sph = 0;
#pragma unroll 1
            for (uint32_t n = 0;; n++) {
                mbar_wait(sb + gk::B_TF + 8 * (n & 1), (n >> 1) & 1);
                const uint32_t task = __shfl_sync(0xffffffffu, lds32(sb + gk::TASK + 4 * (n & 1)), 0);
                mbar_arrive_w(sb + gk::B_TE + 8 * (n & 1));
                const uint32_t ty = task >> 16, grp = (task >> 8) & 255, idx = task & 255;
                if (ty == gk::T_DONE) break;
                const CUtensorMap* m = ty == 0 ? &mp.qkv : (ty == 1 ? &mp.oa : (ty == 3 ? &mp.ob : &mp.out));
                int nb, r0, c0, sh;
                if (ty == 1) { nb = 2; r0 = grp * 128; c0 = idx * 64; sh = 0; }
                else if (ty == 3) { nb = grp >= HALF_FROM ? 4 : 8; r0 = grp * 64; c0 = idx * nb * 64; sh = 3; }
                else if (ty == 5) { nb = grp < NWIDE ? 2 : 1; r0 = (2 * NMED + grp) * 64; c0 = 1024 + idx * nb * 64; sh = 1; }
                else if (ty == 4 && grp >= NBIG) { nb = 4; r0 = grp * 128; c0 = 1024 + idx * 128; sh = 1; }
                else { nb = 8; r0 = grp * 128; c0 = idx * 256 + (ty == 4 ? 1024 : 0); sh = 2; }
                mbar_wait(sb + gk::B_SF, sph);
                sph ^= 1;
                if (lane == 0) {
                    for (int i = 0; i < nb; i++)
                        tma2d_store(m, sb + gk::STG + i * 8192, c0 + 64 * (i & ((1 << sh) - 1)), r0 + 64 * (i >> sh));
                    asm volatile("cp.async.bulk.commit_group;" ::: "memory");
                    asm volatile("cp.async.bulk.wait_group.read 0;" ::: "memory");
                    mbar_arrive(sb + gk::B_SE);
                    asm volatile("cp.async.bulk.wait_group 0;" ::: "memory");
                    if (ty == 0 || ty == 1 || ty == 3) {
                        asm volatile("fence.proxy.async.global;" ::: "memory");
                        fence_gpu();
                        red_add_relaxed(ty == 0 ? &gs->cqkv[grp] : (ty == 1 ? &gs->cqkv[16 + grp] : &gs->cob[grp]), ty == 3 ? nb >> 2 : 1);
                    }
                }
                __syncwarp();
            }
            if (lane == 0 && atomicAdd(&gs->exits, 1u) == gridDim.x - 1) st_relaxed32(&g_epoch, epoch + 1);
        } else if (cw == 10) {
            if (blockIdx.x == 0) {
                unsigned it = 0;
                while (__any_sync(0xffffffffu, ld_relaxed32(&gs->segdone[31][0]) < RCTAS)) { __nanosleep(1000); if (++it > 3000000) __trap(); }
            }
        } else {
#pragma unroll 1
            for (uint32_t n = 0;; n++) {
                if (n) mbar_wait(sb + gk::B_NEXT, (n - 1) & 1);
                mbar_wait(sb + gk::B_TE + 8 * (n & 1), ((n >> 1) & 1) ^ 1);
                const uint32_t task = g_schedule(lane, gs);
                sts32(sb + gk::TASK + 4 * (n & 1), task);
                __syncwarp();
                mbar_arrive_w(sb + gk::B_TF + 8 * (n & 1));
                if ((task >> 16) == gk::T_DONE) break;
            }
        }
    }
}

typedef CUresult (*EncodeTiledFn)(CUtensorMap*, CUtensorMapDataType, cuuint32_t, void*, const cuuint64_t*, const cuuint64_t*,
                                  const cuuint32_t*, const cuuint32_t*, CUtensorMapInterleave, CUtensorMapSwizzle,
                                  CUtensorMapL2promotion, CUtensorMapFloatOOBfill);
static EncodeTiledFn get_encode_fn() {
    static EncodeTiledFn fn = nullptr;
    if (!fn) {
        void* p = nullptr;
        cudaDriverEntryPointQueryResult q;
        cudaGetDriverEntryPoint("cuTensorMapEncodeTiled", &p, cudaEnableDefault, &q);
        fn = (EncodeTiledFn)p;
    }
    return fn;
}
static CUtensorMap make_map(const void* ptr, uint64_t rows, uint64_t cols, uint64_t ld, uint32_t brows, uint32_t bcols,
                            CUtensorMapSwizzle swz = CU_TENSOR_MAP_SWIZZLE_128B) {
    CUtensorMap m;
    cuuint64_t dims[2] = {cols, rows};
    cuuint64_t strides[1] = {ld * 2};
    cuuint32_t box[2] = {bcols, brows};
    cuuint32_t es[2] = {1, 1};
    CUresult r = get_encode_fn()(&m, CU_TENSOR_MAP_DATA_TYPE_BFLOAT16, 2, (void*)ptr, dims, strides, box, es,
                                 CU_TENSOR_MAP_INTERLEAVE_NONE, swz, CU_TENSOR_MAP_L2_PROMOTION_L2_256B,
                                 CU_TENSOR_MAP_FLOAT_OOB_FILL_NONE);
    if (r != CUDA_SUCCESS) fprintf(stderr, "tensor map encode failed: %d\n", (int)r);
    return m;
}
static CUtensorMap make_map3(const void* ptr, uint64_t rows, uint64_t cols, uint64_t ld, uint32_t brows, uint32_t nblk) {
    CUtensorMap m;
    cuuint64_t dims[3] = {64, rows, cols / 64};
    cuuint64_t strides[2] = {ld * 2, 128};
    cuuint32_t box[3] = {64, brows, nblk};
    cuuint32_t es[3] = {1, 1, 1};
    CUresult r = get_encode_fn()(&m, CU_TENSOR_MAP_DATA_TYPE_BFLOAT16, 3, (void*)ptr, dims, strides, box, es,
                                 CU_TENSOR_MAP_INTERLEAVE_NONE, CU_TENSOR_MAP_SWIZZLE_128B, CU_TENSOR_MAP_L2_PROMOTION_L2_256B,
                                 CU_TENSOR_MAP_FLOAT_OOB_FILL_NONE);
    if (r != CUDA_SUCCESS) fprintf(stderr, "tensor map encode failed: %d\n", (int)r);
    return m;
}

#define USE_SPARE 1
extern "C" void kernel_launch(void* const* d_in, const int* in_sizes, int n_in, void* d_out, int out_size) {
    const bf16* ax = (const bf16*)d_in[0];
    const bf16* wqkv = (const bf16*)d_in[1];
    const bf16* wo = (const bf16*)d_in[2];
    const bf16* bx = (const bf16*)d_in[3];
    const bf16* mem0 = (const bf16*)d_in[4];
    const bf16* wq = (const bf16*)d_in[5];
    const bf16* wk = (const bf16*)d_in[6];
    const bf16* wv = (const bf16*)d_in[7];
    const bf16* bwo = (const bf16*)d_in[8];
    void *qkvA, *oA, *oB;
    cudaGetSymbolAddress(&qkvA, g_qkvA);
    cudaGetSymbolAddress(&oA, g_oA);
    cudaGetSymbolAddress(&oB, g_oB);
    cudaFuncSetAttribute(r_kernel, cudaFuncAttributeMaxDynamicSharedMemorySize, rk::SMEM_BYTES);
    cudaFuncSetAttribute(g_kernel, cudaFuncAttributeMaxDynamicSharedMemorySize, gk::SMEM_BYTES);

    const CUtensorMap mq = make_map(wq, 1024, 4096, 4096, 64, 64), mk = make_map(wk, 1024, 4096, 4096, 64, 64),
                      mv = make_map(wv, 1024, 4096, 4096, 64, 64),
                      mx = make_map3(bx, 2048, 1024, 1024, 32, 2);
    GMaps gm;
    gm.ax = make_map(ax, 2048, 1024, 1024, 64, 64);
    gm.qkv = make_map(qkvA, 2048, 3072, 3072, 64, 64);
    gm.oa = make_map(oA, 2048, 1024, 1024, 64, 64);
    gm.ob = make_map(oB, 2048, 4096, 4096, 64, 64);
    gm.out = make_map(d_out, 2048, 2048, 2048, 64, 64);
    gm.wqkv = make_map3(wqkv, 1024, 3072, 3072, 64, 4);
    gm.wo = make_map3(wo, 1024, 1024, 1024, 64, 4);
    gm.bwo = make_map3(bwo, 4096, 1024, 1024, 64, 4);
    gm.bwom = make_map3(bwo, 4096, 1024, 1024, 64, 2);
    gm.bwos = make_map(bwo, 4096, 1024, 1024, 128, 64);

    static int spare = -1;
    if (spare < 0) {
        cudaLaunchConfig_t oc = {};
        oc.gridDim = dim3(3, NHEAD + 2); oc.blockDim = dim3(384); oc.dynamicSmemBytes = rk::SMEM_BYTES;
        cudaLaunchAttribute ca[1];
        ca[0].id = cudaLaunchAttributeClusterDimension;
        ca[0].val.clusterDim.x = 3; ca[0].val.clusterDim.y = 2; ca[0].val.clusterDim.z = 1;
        oc.attrs = ca; oc.numAttrs = 1;
        int n = 0;
        spare = cudaOccupancyMaxActiveClusters(&n, r_kernel, &oc) == cudaSuccess && n >= 17 && USE_SPARE;
        (void)cudaGetLastError();
    }
    r_kernel<<<dim3(3, NHEAD + 2 * spare), 384, rk::SMEM_BYTES, cudaStreamPerThread>>>(mq, mk, mv, make_map(bwo, 4096, 1024, 1024, 16, 64), mx, make_map(oB, 2048, 4096, 4096, 32, 64),
                                                                  gm.ob, (bf16*)d_out, mem0);

    cudaLaunchConfig_t cfg = {};
    int sms = 132;
    cudaDeviceGetAttribute(&sms, cudaDevAttrMultiProcessorCount, 0);
    cfg.gridDim = dim3(sms > RCTAS + 8 ? sms - RCTAS : 8);
    cfg.blockDim = dim3(384);
    cfg.dynamicSmemBytes = gk::SMEM_BYTES;
    cfg.stream = cudaStreamPerThread;
    cudaLaunchAttribute at[1];
    at[0].id = cudaLaunchAttributeProgrammaticStreamSerialization;
    at[0].val.programmaticStreamSerializationAllowed = 1;
    cfg.attrs = at;
    cfg.numAttrs = 1;
    cudaLaunchKernelEx(&cfg, g_kernel, gm);
}
```
